```python
import torch

def _softmax(x, axis=-1):
    return torch.softmax(x, dim=axis)

def _gelu(x):
    return torch.nn.functional.gelu(x, approximate='tanh')

def _silu(x):
    return torch.nn.functional.silu(x)

def _sigmoid(x):
    return torch.sigmoid(x)

def _layernorm(x, axis=-1, eps=1e-05):
    m = x.mean(dim=axis, keepdim=True)
    v = x.var(dim=axis, keepdim=True, unbiased=False)
    return (x - m) / torch.sqrt(v + eps)

def _scatter_add(tgt, idx, src, axis=0):
    return tgt.clone().index_add_(axis, idx, src)

def _segment_sum(src, seg, n):
    out = torch.zeros((n,) + src.shape[1:], dtype=src.dtype)
    return out.index_add_(0, seg, src)

def _pad(x, pw):
    flat = tuple((v for pair in reversed(pw) for v in pair))
    return torch.nn.functional.pad(x, flat)
kernel_name = 'adaLN_cond__sliding_block__mixer_channel_mlp__prompt'

def setup_inputs():

    _w = lambda a: (lambda t: t.to(torch.bfloat16) if t.is_floating_point() else t)(torch.as_tensor(a))

    def _A_setup():
        B, S, D = (1, 2048, 640)
        return {'x': _w((lambda *s: torch.randn(*s, dtype=torch.bfloat16) * 0.05)(B, S, D)), 'wqkv': _w((lambda *s: torch.randn(*s, dtype=torch.bfloat16) * 0.05)(D, 3 * D)), 'wo': _w((lambda *s: torch.randn(*s, dtype=torch.bfloat16) * 0.05)(D, D))}
    _A_in = _A_setup()

    def _B_setup():
        B, S, D, F = (1, 2048, 640, 1728)
        return {'x': _w((lambda *s: torch.randn(*s, dtype=torch.bfloat16) * 0.05)(B, S, D)), 'w1': _w((lambda *s: torch.randn(*s, dtype=torch.bfloat16) * 3.2)(D, F) * D ** (-0.5)), 'b1': _w((lambda *s: torch.randn(*s, dtype=torch.bfloat16) * 1.6)(F)), 'w2': _w((lambda *s: torch.randn(*s, dtype=torch.bfloat16) * 0.4)(F, D) * F ** (-0.5)), 'b2': _w((lambda *s: torch.randn(*s, dtype=torch.bfloat16) * 0.8)(D))}
    _B_in = _B_setup()
    return {'A_x': _A_in['x'], 'A_wqkv': _A_in['wqkv'], 'A_wo': _A_in['wo'], 'B_x': _B_in['x'], 'B_w1': _B_in['w1'], 'B_b1': _B_in['b1'], 'B_w2': _B_in['w2'], 'B_b2': _B_in['b2'], 'c': _w((lambda *s: torch.randn(*s, dtype=torch.bfloat16) * 0.1)(1, 640) * 8.0), 'w_mod': _w((lambda *s: torch.randn(*s, dtype=torch.bfloat16) * 0.1)(640, 6 * 640) * 640 ** (-0.5) * 8.0)}

def reference(A_x, A_wqkv, A_wo, B_x, B_w1, B_b1, B_w2, B_b2, c, w_mod):

    def _A_ref(x, wqkv, wo):
        B, S, D = x.shape
        H = 32
        Dh = D // H
        W = 256
        qkv = (lambda x, *d: x.permute(*d))((x @ wqkv).reshape(B, S, 3, H, Dh), 2, 0, 3, 1, 4)
        q, k, v = (qkv[0], qkv[1], qkv[2])
        scores = torch.einsum('bhqd,bhkd->bhqk', q, k) * Dh ** (-0.5)
        idx = torch.arange(S)
        mask = (idx[:, None] - idx[None, :] >= 0) & (idx[:, None] - idx[None, :] < W)
        scores = torch.where(mask[None, None], scores, -1000000000.0)
        p = _softmax(scores, axis=-1)
        o = torch.einsum('bhqk,bhkd->bhqd', p, v)
        return (lambda x, *d: x.permute(*d))(o, 0, 2, 1, 3).reshape(B, S, D) @ wo

    def _B_ref(x, w1, b1, w2, b2):
        y = _layernorm(x, axis=-1)
        h = _gelu(torch.einsum('bsd,df->bsf', y, w1) + b1)
        return torch.einsum('bsf,fd->bsd', h, w2) + b2
    x = A_x
    mod = (_silu(c) @ w_mod).reshape(c.shape[0], 6, 1, -1)
    sa, ca, ga, sb, cb, gb = (mod[:, 0].clone(), mod[:, 1].clone(), mod[:, 2].clone(), mod[:, 3].clone(), mod[:, 4].clone(), mod[:, 5].clone())
    h = _layernorm(x, axis=-1) * (1 + ca) + sa
    x = x + ga * _A_ref(h, A_wqkv, A_wo)
    h = _layernorm(x, axis=-1) * (1 + cb) + sb
    x = x + gb * _B_ref(h, B_w1, B_b1, B_w2, B_b2)
    return x
```

```cpp
#include <cuda_runtime.h>
#include <cuda_bf16.h>
#include <cuda.h>
#include <stdint.h>

#define DEVI __device__ __forceinline__
typedef __nv_bfloat16 bf16;

namespace {

constexpr int SEQ = 2048, DM = 640;
constexpr int NCTA = 132;
constexpr int KV_ATOM = 2816;
constexpr int KV_HALF = 8 * KV_ATOM;
constexpr int KV_IMG = 2 * KV_HALF;
constexpr int SPIN_LIMIT = 1 << 17;

constexpr int OFF_A = 0;
constexpr int OFF_B = 65536;
constexpr int SLOT_B = 28672;
constexpr int SLOT_B1 = 30720;
constexpr int OFF_SLAB = 190464;
constexpr int OFF_C = OFF_SLAB + 20480;
constexpr int OFF_WO = 122880;
constexpr int OFF_T = 225280;
constexpr int OFF_TAB = OFF_T;
constexpr int OFF_GB = OFF_TAB + 2560;
constexpr int OFF_B1T = OFF_GB + 1280;
constexpr int OFF_GA = OFF_B1T + 896;
constexpr int OFF_CST = OFF_GA + 320;
constexpr int OFF_RED = OFF_CST + 64;
constexpr int OFF_BAR = OFF_RED + 704;
constexpr int NBAR = 77;
constexpr int OFF_EP = OFF_BAR + NBAR * 8;
constexpr int SMEM_BYTES = OFF_EP + 16;
static_assert(SMEM_BYTES <= 232448, "smem");

constexpr int B_FULL1 = 0, B_SLAB = 4, B_SLABFREE = 5,
              B_EMPTY1 = 6, B_WOB = 10, B_AF = 12, B_AE = 16, B_BF = 20, B_BE = 25, B_QKVDONE = 30, B_ATTDONE = 31,
              B_TAB2 = 32, B_RF = 33  , B_PEER = 38, B_KV = 39  , B_OPUB = 45, B_XPUB = 46,
              B_SLAB2 = 47, B_SLAB2FREE = 48, B_SF = 49  , B_SE = 59  , B_RX = 65  ,
              B_FIN = 75, B_SPUB = 76;
constexpr int NB_SETUP = 1, NB_CONS = 2, NB_PG = 4, NB_GEMV = 5, NB_P23 = 6, NB_SKEW = 7, NB_VOTE = 8;

struct alignas(64) TMaps {
  CUtensorMap x, wqkv_m, wqkv_r, wo, o, x1, w1_m, w1_r, w2_a, w2_b, w2_r, part, wmod;
};
struct Params {
  const bf16 *x, *wo, *w1, *b1, *w2, *b2, *c;
  bf16* out;
  int use_smid;
};

__device__ uint4 g_kv[128 * (KV_IMG / 16)];
__device__ uint4 g_o[SEQ * DM / 8];
__device__ uint4 g_x1[SEQ * DM / 8];
__device__ uint4 g_part[4 * SEQ * DM / 8];
__device__ uint4 g_stats[SEQ * 8 * 2];
__device__ uint4 g_fin[SEQ];
__device__ unsigned long long g_mod[1920];
__device__ unsigned long long g_st1[SEQ];
__device__ unsigned int g_flag_kv[128 * 16];
__device__ unsigned int g_flag_o[16 * 32];
__device__ unsigned int g_flag_x1[16 * 32];
__device__ unsigned long long g_ticket;
#define PSTAMP(slot) do {} while (0)
#define CSTAMP(slot) do {} while (0)
#define GSTAMP(slot) do {} while (0)
#define DSTAMP(slot, dep) do {} while (0)

DEVI uint32_t slot_b(int s) { return OFF_B + (s < 2 ? s : 6 - s) * SLOT_B; }
DEVI uint32_t s2u(const void* p) { return (uint32_t)__cvta_generic_to_shared(p); }
DEVI void mbar_init(uint32_t b, uint32_t c) { asm volatile("mbarrier.init.shared::cta.b64 [%0], %1;" ::"r"(b), "r"(c) : "memory"); }
DEVI void init_barriers(uint32_t bar, int k) {
  constexpr unsigned long long M8 = (0xfull << B_EMPTY1) | (0xfull << B_AE) | (0x1full << B_BE) | (1ull << B_QKVDONE) |
                                    (1ull << B_ATTDONE) | (1ull << B_OPUB) | (1ull << B_XPUB) | (1ull << B_PEER);
  constexpr unsigned long long M128 = 3ull << (B_KV + 4), M4 = 0x3ffull << B_SF;
#pragma unroll 1
  for (int i = 6 + k; i < NBAR; i += 11)
    mbar_init(bar + 8 * i, i == B_SPUB ? 8 : i >= B_SE ? 1 : (M8 >> i & 1) ? 8 : (M128 >> i & 1) ? 128 : (M4 >> i & 1) ? 4 : i == B_TAB2 ? 64 : i == B_SLAB2FREE ? 2 : 1);
  asm volatile("fence.mbarrier_init.release.cluster;" ::: "memory");
}
DEVI void mbar_expect(uint32_t b, uint32_t bytes) {
  asm volatile("mbarrier.arrive.expect_tx.shared::cta.b64 _, [%0], %1;" ::"r"(b), "r"(bytes) : "memory");
}
DEVI void mbar_arrive(uint32_t b) { asm volatile("mbarrier.arrive.shared::cta.b64 _, [%0];" ::"r"(b) : "memory"); }
DEVI void mbar_wait(uint32_t b, uint32_t parity) {
  asm volatile(
      "{\n.reg .pred p;\n.reg .u32 c;\nmov.u32 c, %2;\n"
      "W: mbarrier.try_wait.parity.shared::cta.b64 p, [%0], %1;\n@p bra D;\n"
      "sub.u32 c, c, 1;\nsetp.ne.u32 p, c, 0;\n@p bra W;\nD:\n}" ::"r"(b), "r"(parity), "n"(SPIN_LIMIT) : "memory");
}
DEVI void mbar_wait2(uint32_t b0, uint32_t p0, uint32_t b1, uint32_t p1) {
  asm volatile(
      "{\n.reg .pred p, q;\n.reg .u32 c;\nmov.u32 c, %4;\n"
      "W: mbarrier.try_wait.parity.shared::cta.b64 p, [%0], %1;\n"
      "mbarrier.try_wait.parity.shared::cta.b64 q, [%2], %3;\n"
      "and.pred p, p, q;\n@p bra D;\n"
      "sub.u32 c, c, 1;\nsetp.ne.u32 p, c, 0;\n@p bra W;\nD:\n}" ::"r"(b0), "r"(p0), "r"(b1), "r"(p1), "n"(SPIN_LIMIT) : "memory");
}
DEVI bool mbar_test(uint32_t b, uint32_t parity) {
  uint32_t ok;
  asm volatile("{\n.reg .pred p;\nmbarrier.test_wait.parity.shared::cta.b64 p, [%1], %2;\nselp.u32 %0, 1, 0, p;\n}"
               : "=r"(ok) : "r"(b), "r"(parity) : "memory");
  return ok;
}
DEVI void bar_sync(int id, int n) { asm volatile("bar.sync %0, %1;" ::"r"(id), "r"(n) : "memory"); }
DEVI void bar_arrive(int id, int n) { asm volatile("bar.arrive %0, %1;" ::"r"(id), "r"(n) : "memory"); }
DEVI void poll_ge(const unsigned int* p, unsigned int target) {
  unsigned int v;
  int it = 0;
  do {
    asm volatile("ld.acquire.gpu.global.u32 %0, [%1];" : "=r"(v) : "l"(p) : "memory");
  } while ((int)(v - target) < 0 && ++it < SPIN_LIMIT);
}
DEVI void red_release(unsigned int* p) { asm volatile("red.release.gpu.global.add.u32 [%0], 1;" ::"l"(p) : "memory"); }
DEVI void ll_store16(uint4* p, float a, float b, float c, uint32_t tag) {
  asm volatile("{\n.reg .b128 v;\nmov.b128 v, {%1, %2};\nst.relaxed.gpu.global.b128 [%0], v;\n}" ::"l"(p),
               "l"(((unsigned long long)__float_as_uint(b) << 32) | __float_as_uint(a)),
               "l"(((unsigned long long)tag << 32) | __float_as_uint(c)) : "memory");
}
DEVI uint4 ll_load16(const uint4* p) {
  unsigned long long a, b;
  asm volatile("{\n.reg .b128 v;\nld.relaxed.gpu.global.b128 v, [%2];\nmov.b128 {%0, %1}, v;\n}" : "=l"(a), "=l"(b) : "l"(p) : "memory");
  return make_uint4((uint32_t)a, (uint32_t)(a >> 32), (uint32_t)b, (uint32_t)(b >> 32));
}
DEVI void ll_store(unsigned long long* p, uint32_t data, uint32_t tag) {
  asm volatile("st.relaxed.gpu.global.u64 [%0], %1;" ::"l"(p), "l"(((unsigned long long)tag << 32) | data) : "memory");
}
DEVI void fence_async_gmem() { asm volatile("fence.proxy.async.global;" ::: "memory"); }
DEVI void fence_async_smem() { asm volatile("fence.proxy.async.shared::cta;" ::: "memory"); }
DEVI void tma2(uint32_t dst, const CUtensorMap* m, uint32_t bar, int c0, int c1) {
  asm volatile("cp.async.bulk.tensor.2d.shared::cluster.global.mbarrier::complete_tx::bytes [%0], [%1, {%3, %4}], [%2];"
               ::"r"(dst), "l"(m), "r"(bar), "r"(c0), "r"(c1) : "memory");
}
DEVI void tma3(uint32_t dst, const CUtensorMap* m, uint32_t bar, int c0, int c1, int c2) {
  asm volatile("cp.async.bulk.tensor.3d.shared::cluster.global.mbarrier::complete_tx::bytes [%0], [%1, {%3, %4, %5}], [%2];"
               ::"r"(dst), "l"(m), "r"(bar), "r"(c0), "r"(c1), "r"(c2) : "memory");
}
DEVI void tma2_store(const CUtensorMap* m, uint32_t src, int c0, int c1) {
  asm volatile("cp.async.bulk.tensor.2d.global.shared::cta.bulk_group [%0, {%2, %3}], [%1];" ::"l"(m), "r"(src), "r"(c0), "r"(c1) : "memory");
}
DEVI void bulk_load(uint32_t dst, const void* src, uint32_t bytes, uint32_t bar) {
  asm volatile("cp.async.bulk.shared::cluster.global.mbarrier::complete_tx::bytes [%0], [%1], %2, [%3];"
               ::"r"(dst), "l"(src), "r"(bytes), "r"(bar) : "memory");
}
DEVI void bulk_store(void* dst, uint32_t src, uint32_t bytes) {
  asm volatile("cp.async.bulk.global.shared::cta.bulk_group [%0], [%1], %2;" ::"l"(dst), "r"(src), "r"(bytes) : "memory");
}
DEVI void bulk_commit() { asm volatile("cp.async.bulk.commit_group;" ::: "memory"); }
DEVI void bulk_wait1() { asm volatile("cp.async.bulk.wait_group 1;" ::: "memory"); }
DEVI void bulk_wait0() { asm volatile("cp.async.bulk.wait_group 0;" ::: "memory"); }
DEVI void l2_prefetch(const void* p, uint32_t bytes) {
  asm volatile("cp.async.bulk.prefetch.L2.global [%0], %1;" ::"l"(p), "r"(bytes) : "memory");
}
DEVI uint32_t dlo(uint32_t addr, uint32_t lbo) { return ((addr & 0x3FFFF) >> 4) | ((lbo >> 4) << 16); }
DEVI uint64_t mkdesc(uint32_t lo, uint32_t off, uint32_t sbo, uint32_t sw) {
  return (uint64_t)(lo + (off >> 4)) | ((uint64_t)((sbo >> 4) | (sw << 30)) << 32);
}
#define WG_FENCE() asm volatile("wgmma.fence.sync.aligned;" ::: "memory")
#define WG_COMMIT() asm volatile("wgmma.commit_group.sync.aligned;" ::: "memory")
#define WG_WAIT(n) asm volatile("wgmma.wait_group.sync.aligned %0;" ::"n"(n) : "memory")
DEVI void ldsm4(uint32_t (&r)[4], uint32_t addr) {
  asm volatile("ldmatrix.sync.aligned.m8n8.x4.shared.b16 {%0,%1,%2,%3}, [%4];"
               : "=r"(r[0]), "=r"(r[1]), "=r"(r[2]), "=r"(r[3]) : "r"(addr) : "memory");
}
DEVI void stsm4(uint32_t addr, uint32_t a, uint32_t b, uint32_t c, uint32_t d) {
  asm volatile("stmatrix.sync.aligned.m8n8.x4.shared.b16 [%0], {%1,%2,%3,%4};" ::"r"(addr), "r"(a), "r"(b), "r"(c), "r"(d) : "memory");
}
DEVI uint4 lds128(uint32_t a) {
  uint4 v;
  asm volatile("ld.shared.v4.u32 {%0,%1,%2,%3}, [%4];" : "=r"(v.x), "=r"(v.y), "=r"(v.z), "=r"(v.w) : "r"(a) : "memory");
  return v;
}
DEVI uint2 lds64(uint32_t a) {
  uint2 v;
  asm volatile("ld.shared.v2.u32 {%0,%1}, [%2];" : "=r"(v.x), "=r"(v.y) : "r"(a) : "memory");
  return v;
}
DEVI uint32_t lds32(uint32_t a) {
  uint32_t v;
  asm volatile("ld.shared.u32 %0, [%1];" : "=r"(v) : "r"(a) : "memory");
  return v;
}
DEVI void sts32(uint32_t a, uint32_t v) { asm volatile("st.shared.u32 [%0], %1;" ::"r"(a), "r"(v) : "memory"); }
DEVI void sts64(uint32_t a, uint32_t x, uint32_t y) { asm volatile("st.shared.v2.u32 [%0], {%1,%2};" ::"r"(a), "r"(x), "r"(y) : "memory"); }
DEVI void sts128(uint32_t a, uint4 v) {
  asm volatile("st.shared.v4.u32 [%0], {%1,%2,%3,%4};" ::"r"(a), "r"(v.x), "r"(v.y), "r"(v.z), "r"(v.w) : "memory");
}
DEVI uint4 ldg_nc(const void* p) {
  uint4 v;
  asm volatile("ld.global.nc.L1::no_allocate.v4.u32 {%0,%1,%2,%3}, [%4];" : "=r"(v.x), "=r"(v.y), "=r"(v.z), "=r"(v.w) : "l"(p));
  return v;
}
DEVI uint4 ldg_cg(const void* p) {
  uint4 v;
  asm volatile("ld.global.cg.v4.u32 {%0,%1,%2,%3}, [%4];" : "=r"(v.x), "=r"(v.y), "=r"(v.z), "=r"(v.w) : "l"(p) : "memory");
  return v;
}
DEVI void stg128(void* p, uint4 v) {
  asm volatile("st.global.v4.u32 [%0], {%1,%2,%3,%4};" ::"l"(p), "r"(v.x), "r"(v.y), "r"(v.z), "r"(v.w) : "memory");
}
DEVI uint32_t pack2(float lo, float hi) {
  uint32_t r;
  asm("cvt.rn.bf16x2.f32 %0, %1, %2;" : "=r"(r) : "f"(hi), "f"(lo));
  return r;
}
DEVI float bf_lo(uint32_t v) { return __uint_as_float(v << 16); }
DEVI float bf_hi(uint32_t v) { return __uint_as_float(v & 0xffff0000u); }
DEVI uint32_t hfma2(uint32_t a, uint32_t b, uint32_t c) {
  uint32_t r;
  asm("fma.rn.bf16x2 %0, %1, %2, %3;" : "=r"(r) : "r"(a), "r"(b), "r"(c));
  return r;
}
DEVI float ex2(float x) {
  float r;
  asm("ex2.approx.ftz.f32 %0, %1;" : "=f"(r) : "f"(x));
  return r;
}
DEVI float ex2v(float x) {
  float r;
  asm volatile("ex2.approx.ftz.f32 %0, %1;" : "=f"(r) : "f"(x));
  return r;
}
DEVI float ex2p(float x) {
  float y;
  asm("fma.rn.sat.f32 %0, %1, %2, %3;" : "=f"(y) : "f"(x), "f"(1.0f / 254.0f), "f"(126.0f / 254.0f));
  const float t = fmaf(y, 254.0f, 12582912.0f - 126.0f);
  const float f = fmaf(y, 254.0f, (12582912.0f - 126.0f) - t);
  const float p = fmaf(fmaf(fmaf(f, 0.0551716611f, 0.2426111251f), f, 0.6932609677f), f, 0.9999280572f);
  return __uint_as_float(__float_as_uint(p) + (__float_as_uint(t) << 23));
}
DEVI float gelu_half(float z) {
  float u = z * fmaf(z * z, 8.f * 0.0356774081f, 2.f * 0.7978845608f);
  float t;
  asm("tanh.approx.f32 %0, %1;" : "=f"(t) : "f"(u));
  return fmaf(z, t, z);
}
DEVI float silu_bf(float x) {
  float s = __fdividef(x, 1.0f + ex2(-1.4426950408889634f * x));
  return bf_lo(pack2(s, 0.f) & 0xffffu);
}

__device__ __forceinline__ void wgmma_rs_n192_t1(float (&d)[96], const uint32_t (&a)[4], uint64_t db, int sd) {
  asm volatile("{\n.reg .pred p;\nsetp.ne.b32 p, %101, 0;\nwgmma.mma_async.sync.aligned.m64n192k16.f32.bf16.bf16 "
    "{%0, %1, %2, %3, %4, %5, %6, %7, %8, %9, %10, %11, %12, %13, %14, %15, %16, %17, %18, %19, %20, %21, %22, %23, %24, %25, %26, %27, %28, %29, %30, %31, %32, %33, %34, %35, %36, %37, %38, %39, %40, %41, %42, %43, %44, %45, %46, %47, %48, %49, %50, %51, %52, %53, %54, %55, %56, %57, %58, %59, %60, %61, %62, %63, %64, %65, %66, %67, %68, %69, %70, %71, %72, %73, %74, %75, %76, %77, %78, %79, %80, %81, %82, %83, %84, %85, %86, %87, %88, %89, %90, %91, %92, %93, %94, %95}, {%96, %97, %98, %99}, %100, p, 1, 1, 1;\n}\n"
    : "+f"(d[0]), "+f"(d[1]), "+f"(d[2]), "+f"(d[3]), "+f"(d[4]), "+f"(d[5]), "+f"(d[6]), "+f"(d[7]), "+f"(d[8]), "+f"(d[9]), "+f"(d[10]), "+f"(d[11]), "+f"(d[12]), "+f"(d[13]), "+f"(d[14]), "+f"(d[15]), "+f"(d[16]), "+f"(d[17]), "+f"(d[18]), "+f"(d[19]), "+f"(d[20]), "+f"(d[21]), "+f"(d[22]), "+f"(d[23]), "+f"(d[24]), "+f"(d[25]), "+f"(d[26]), "+f"(d[27]), "+f"(d[28]), "+f"(d[29]), "+f"(d[30]), "+f"(d[31]), "+f"(d[32]), "+f"(d[33]), "+f"(d[34]), "+f"(d[35]), "+f"(d[36]), "+f"(d[37]), "+f"(d[38]), "+f"(d[39]), "+f"(d[40]), "+f"(d[41]), "+f"(d[42]), "+f"(d[43]), "+f"(d[44]), "+f"(d[45]), "+f"(d[46]), "+f"(d[47]), "+f"(d[48]), "+f"(d[49]), "+f"(d[50]), "+f"(d[51]), "+f"(d[52]), "+f"(d[53]), "+f"(d[54]), "+f"(d[55]), "+f"(d[56]), "+f"(d[57]), "+f"(d[58]), "+f"(d[59]), "+f"(d[60]), "+f"(d[61]), "+f"(d[62]), "+f"(d[63]), "+f"(d[64]), "+f"(d[65]), "+f"(d[66]), "+f"(d[67]), "+f"(d[68]), "+f"(d[69]), "+f"(d[70]), "+f"(d[71]), "+f"(d[72]), "+f"(d[73]), "+f"(d[74]), "+f"(d[75]), "+f"(d[76]), "+f"(d[77]), "+f"(d[78]), "+f"(d[79]), "+f"(d[80]), "+f"(d[81]), "+f"(d[82]), "+f"(d[83]), "+f"(d[84]), "+f"(d[85]), "+f"(d[86]), "+f"(d[87]), "+f"(d[88]), "+f"(d[89]), "+f"(d[90]), "+f"(d[91]), "+f"(d[92]), "+f"(d[93]), "+f"(d[94]), "+f"(d[95])
    : "r"(a[0]), "r"(a[1]), "r"(a[2]), "r"(a[3]), "l"(db), "r"(sd));
}
__device__ __forceinline__ void wgmma_rs_n48_t1(float (&d)[24], const uint32_t (&a)[4], uint64_t db, int sd) {
  asm volatile("{\n.reg .pred p;\nsetp.ne.b32 p, %29, 0;\nwgmma.mma_async.sync.aligned.m64n48k16.f32.bf16.bf16 "
    "{%0, %1, %2, %3, %4, %5, %6, %7, %8, %9, %10, %11, %12, %13, %14, %15, %16, %17, %18, %19, %20, %21, %22, %23}, {%24, %25, %26, %27}, %28, p, 1, 1, 1;\n}\n"
    : "+f"(d[0]), "+f"(d[1]), "+f"(d[2]), "+f"(d[3]), "+f"(d[4]), "+f"(d[5]), "+f"(d[6]), "+f"(d[7]), "+f"(d[8]), "+f"(d[9]), "+f"(d[10]), "+f"(d[11]), "+f"(d[12]), "+f"(d[13]), "+f"(d[14]), "+f"(d[15]), "+f"(d[16]), "+f"(d[17]), "+f"(d[18]), "+f"(d[19]), "+f"(d[20]), "+f"(d[21]), "+f"(d[22]), "+f"(d[23])
    : "r"(a[0]), "r"(a[1]), "r"(a[2]), "r"(a[3]), "l"(db), "r"(sd));
}
__device__ __forceinline__ void wgmma_rs_n64_t0(float (&d)[32], const uint32_t (&a)[4], uint64_t db, int sd) {
  asm volatile("{\n.reg .pred p;\nsetp.ne.b32 p, %37, 0;\nwgmma.mma_async.sync.aligned.m64n64k16.f32.bf16.bf16 "
    "{%0, %1, %2, %3, %4, %5, %6, %7, %8, %9, %10, %11, %12, %13, %14, %15, %16, %17, %18, %19, %20, %21, %22, %23, %24, %25, %26, %27, %28, %29, %30, %31}, {%32, %33, %34, %35}, %36, p, 1, 1, 0;\n}\n"
    : "+f"(d[0]), "+f"(d[1]), "+f"(d[2]), "+f"(d[3]), "+f"(d[4]), "+f"(d[5]), "+f"(d[6]), "+f"(d[7]), "+f"(d[8]), "+f"(d[9]), "+f"(d[10]), "+f"(d[11]), "+f"(d[12]), "+f"(d[13]), "+f"(d[14]), "+f"(d[15]), "+f"(d[16]), "+f"(d[17]), "+f"(d[18]), "+f"(d[19]), "+f"(d[20]), "+f"(d[21]), "+f"(d[22]), "+f"(d[23]), "+f"(d[24]), "+f"(d[25]), "+f"(d[26]), "+f"(d[27]), "+f"(d[28]), "+f"(d[29]), "+f"(d[30]), "+f"(d[31])
    : "r"(a[0]), "r"(a[1]), "r"(a[2]), "r"(a[3]), "l"(db), "r"(sd));
}
__device__ __forceinline__ void wgmma_rs_n24_t1(float (&d)[12], const uint32_t (&a)[4], uint64_t db, int sd) {
  asm volatile("{\n.reg .pred p;\nsetp.ne.b32 p, %17, 0;\nwgmma.mma_async.sync.aligned.m64n24k16.f32.bf16.bf16 "
    "{%0, %1, %2, %3, %4, %5, %6, %7, %8, %9, %10, %11}, {%12, %13, %14, %15}, %16, p, 1, 1, 1;\n}\n"
    : "+f"(d[0]), "+f"(d[1]), "+f"(d[2]), "+f"(d[3]), "+f"(d[4]), "+f"(d[5]), "+f"(d[6]), "+f"(d[7]), "+f"(d[8]), "+f"(d[9]), "+f"(d[10]), "+f"(d[11])
    : "r"(a[0]), "r"(a[1]), "r"(a[2]), "r"(a[3]), "l"(db), "r"(sd));
}
__device__ __forceinline__ void wgmma_ss_n80_t1(float (&d)[40], uint64_t da, uint64_t db, int sd) {
  asm volatile("{\n.reg .pred p;\nsetp.ne.b32 p, %42, 0;\nwgmma.mma_async.sync.aligned.m64n80k16.f32.bf16.bf16 "
    "{%0, %1, %2, %3, %4, %5, %6, %7, %8, %9, %10, %11, %12, %13, %14, %15, %16, %17, %18, %19, %20, %21, %22, %23, %24, %25, %26, %27, %28, %29, %30, %31, %32, %33, %34, %35, %36, %37, %38, %39}, %40, %41, p, 1, 1, 0, 1;\n}\n"
    : "+f"(d[0]), "+f"(d[1]), "+f"(d[2]), "+f"(d[3]), "+f"(d[4]), "+f"(d[5]), "+f"(d[6]), "+f"(d[7]), "+f"(d[8]), "+f"(d[9]), "+f"(d[10]), "+f"(d[11]), "+f"(d[12]), "+f"(d[13]), "+f"(d[14]), "+f"(d[15]), "+f"(d[16]), "+f"(d[17]), "+f"(d[18]), "+f"(d[19]), "+f"(d[20]), "+f"(d[21]), "+f"(d[22]), "+f"(d[23]), "+f"(d[24]), "+f"(d[25]), "+f"(d[26]), "+f"(d[27]), "+f"(d[28]), "+f"(d[29]), "+f"(d[30]), "+f"(d[31]), "+f"(d[32]), "+f"(d[33]), "+f"(d[34]), "+f"(d[35]), "+f"(d[36]), "+f"(d[37]), "+f"(d[38]), "+f"(d[39])
    : "l"(da), "l"(db), "r"(sd));
}
__device__ __forceinline__ void wgmma_rs_n32_t1(float (&d)[16], const uint32_t (&a)[4], uint64_t db, int sd) {
  asm volatile("{\n.reg .pred p;\nsetp.ne.b32 p, %21, 0;\nwgmma.mma_async.sync.aligned.m64n32k16.f32.bf16.bf16 "
    "{%0, %1, %2, %3, %4, %5, %6, %7, %8, %9, %10, %11, %12, %13, %14, %15}, {%16, %17, %18, %19}, %20, p, 1, 1, 1;\n}\n"
    : "+f"(d[0]), "+f"(d[1]), "+f"(d[2]), "+f"(d[3]), "+f"(d[4]), "+f"(d[5]), "+f"(d[6]), "+f"(d[7]), "+f"(d[8]), "+f"(d[9]), "+f"(d[10]), "+f"(d[11]), "+f"(d[12]), "+f"(d[13]), "+f"(d[14]), "+f"(d[15])
    : "r"(a[0]), "r"(a[1]), "r"(a[2]), "r"(a[3]), "l"(db), "r"(sd));
}
__device__ __forceinline__ void wgmma_rs_n128_t1(float (&d)[64], const uint32_t (&a)[4], uint64_t db, int sd) {
  asm volatile("{\n.reg .pred p;\nsetp.ne.b32 p, %69, 0;\nwgmma.mma_async.sync.aligned.m64n128k16.f32.bf16.bf16 "
    "{%0, %1, %2, %3, %4, %5, %6, %7, %8, %9, %10, %11, %12, %13, %14, %15, %16, %17, %18, %19, %20, %21, %22, %23, %24, %25, %26, %27, %28, %29, %30, %31, %32, %33, %34, %35, %36, %37, %38, %39, %40, %41, %42, %43, %44, %45, %46, %47, %48, %49, %50, %51, %52, %53, %54, %55, %56, %57, %58, %59, %60, %61, %62, %63}, {%64, %65, %66, %67}, %68, p, 1, 1, 1;\n}\n"
    : "+f"(d[0]), "+f"(d[1]), "+f"(d[2]), "+f"(d[3]), "+f"(d[4]), "+f"(d[5]), "+f"(d[6]), "+f"(d[7]), "+f"(d[8]), "+f"(d[9]), "+f"(d[10]), "+f"(d[11]), "+f"(d[12]), "+f"(d[13]), "+f"(d[14]), "+f"(d[15]), "+f"(d[16]), "+f"(d[17]), "+f"(d[18]), "+f"(d[19]), "+f"(d[20]), "+f"(d[21]), "+f"(d[22]), "+f"(d[23]), "+f"(d[24]), "+f"(d[25]), "+f"(d[26]), "+f"(d[27]), "+f"(d[28]), "+f"(d[29]), "+f"(d[30]), "+f"(d[31]), "+f"(d[32]), "+f"(d[33]), "+f"(d[34]), "+f"(d[35]), "+f"(d[36]), "+f"(d[37]), "+f"(d[38]), "+f"(d[39]), "+f"(d[40]), "+f"(d[41]), "+f"(d[42]), "+f"(d[43]), "+f"(d[44]), "+f"(d[45]), "+f"(d[46]), "+f"(d[47]), "+f"(d[48]), "+f"(d[49]), "+f"(d[50]), "+f"(d[51]), "+f"(d[52]), "+f"(d[53]), "+f"(d[54]), "+f"(d[55]), "+f"(d[56]), "+f"(d[57]), "+f"(d[58]), "+f"(d[59]), "+f"(d[60]), "+f"(d[61]), "+f"(d[62]), "+f"(d[63])
    : "r"(a[0]), "r"(a[1]), "r"(a[2]), "r"(a[3]), "l"(db), "r"(sd));
}
__device__ __forceinline__ void wgmma_rz_n64_t0(float (&d)[32], const uint32_t (&a)[4], uint64_t db) {
  asm volatile("wgmma.mma_async.sync.aligned.m64n64k16.f32.bf16.bf16 "
    "{%0, %1, %2, %3, %4, %5, %6, %7, %8, %9, %10, %11, %12, %13, %14, %15, %16, %17, %18, %19, %20, %21, %22, %23, %24, %25, %26, %27, %28, %29, %30, %31}, {%32, %33, %34, %35}, %36, 0, 1, 1, 0;\n"
    : "=f"(d[0]), "=f"(d[1]), "=f"(d[2]), "=f"(d[3]), "=f"(d[4]), "=f"(d[5]), "=f"(d[6]), "=f"(d[7]), "=f"(d[8]), "=f"(d[9]), "=f"(d[10]), "=f"(d[11]), "=f"(d[12]), "=f"(d[13]), "=f"(d[14]), "=f"(d[15]), "=f"(d[16]), "=f"(d[17]), "=f"(d[18]), "=f"(d[19]), "=f"(d[20]), "=f"(d[21]), "=f"(d[22]), "=f"(d[23]), "=f"(d[24]), "=f"(d[25]), "=f"(d[26]), "=f"(d[27]), "=f"(d[28]), "=f"(d[29]), "=f"(d[30]), "=f"(d[31])
    : "r"(a[0]), "r"(a[1]), "r"(a[2]), "r"(a[3]), "l"(db));
}
__device__ __forceinline__ void wgmma_rz_n128_t1(float (&d)[64], const uint32_t (&a)[4], uint64_t db) {
  asm volatile("wgmma.mma_async.sync.aligned.m64n128k16.f32.bf16.bf16 "
    "{%0, %1, %2, %3, %4, %5, %6, %7, %8, %9, %10, %11, %12, %13, %14, %15, %16, %17, %18, %19, %20, %21, %22, %23, %24, %25, %26, %27, %28, %29, %30, %31, %32, %33, %34, %35, %36, %37, %38, %39, %40, %41, %42, %43, %44, %45, %46, %47, %48, %49, %50, %51, %52, %53, %54, %55, %56, %57, %58, %59, %60, %61, %62, %63}, {%64, %65, %66, %67}, %68, 0, 1, 1, 1;\n"
    : "=f"(d[0]), "=f"(d[1]), "=f"(d[2]), "=f"(d[3]), "=f"(d[4]), "=f"(d[5]), "=f"(d[6]), "=f"(d[7]), "=f"(d[8]), "=f"(d[9]), "=f"(d[10]), "=f"(d[11]), "=f"(d[12]), "=f"(d[13]), "=f"(d[14]), "=f"(d[15]), "=f"(d[16]), "=f"(d[17]), "=f"(d[18]), "=f"(d[19]), "=f"(d[20]), "=f"(d[21]), "=f"(d[22]), "=f"(d[23]), "=f"(d[24]), "=f"(d[25]), "=f"(d[26]), "=f"(d[27]), "=f"(d[28]), "=f"(d[29]), "=f"(d[30]), "=f"(d[31]), "=f"(d[32]), "=f"(d[33]), "=f"(d[34]), "=f"(d[35]), "=f"(d[36]), "=f"(d[37]), "=f"(d[38]), "=f"(d[39]), "=f"(d[40]), "=f"(d[41]), "=f"(d[42]), "=f"(d[43]), "=f"(d[44]), "=f"(d[45]), "=f"(d[46]), "=f"(d[47]), "=f"(d[48]), "=f"(d[49]), "=f"(d[50]), "=f"(d[51]), "=f"(d[52]), "=f"(d[53]), "=f"(d[54]), "=f"(d[55]), "=f"(d[56]), "=f"(d[57]), "=f"(d[58]), "=f"(d[59]), "=f"(d[60]), "=f"(d[61]), "=f"(d[62]), "=f"(d[63])
    : "r"(a[0]), "r"(a[1]), "r"(a[2]), "r"(a[3]), "l"(db));
}

template <int NT>
DEVI void gemv_acc(uint32_t sbase, int t, const float (&sc)[1280 / NT], float (&a)[8]) {
#pragma unroll
  for (int e = 0; e < 8; e++) a[e] = 0.f;
#pragma unroll
  for (int m = 0; m < 1280 / NT; m++) {
    const uint4 wv = lds128(sbase + OFF_SLAB + (t + m * NT) * 16);
    const float s = sc[m];
    a[0] = fmaf(s, bf_lo(wv.x), a[0]); a[1] = fmaf(s, bf_hi(wv.x), a[1]);
    a[2] = fmaf(s, bf_lo(wv.y), a[2]); a[3] = fmaf(s, bf_hi(wv.y), a[3]);
    a[4] = fmaf(s, bf_lo(wv.z), a[4]); a[5] = fmaf(s, bf_hi(wv.z), a[5]);
    a[6] = fmaf(s, bf_lo(wv.w), a[6]); a[7] = fmaf(s, bf_hi(wv.w), a[7]);
  }
}
DEVI void gemv_partial(const float (&a)[8], int lane, uint32_t red_w) {
  const bool b4 = lane & 16, b3 = lane & 8, b2 = lane & 4;
  float b[4], c2[2], d;
#pragma unroll
  for (int e = 0; e < 4; e++) {
    float send = b4 ? a[e] : a[e + 4], keep = b4 ? a[e + 4] : a[e];
    b[e] = keep + __shfl_xor_sync(~0u, send, 16);
  }
#pragma unroll
  for (int e = 0; e < 2; e++) {
    float send = b3 ? b[e] : b[e + 2], keep = b3 ? b[e + 2] : b[e];
    c2[e] = keep + __shfl_xor_sync(~0u, send, 8);
  }
  {
    float send = b2 ? c2[0] : c2[1], keep = b2 ? c2[1] : c2[0];
    d = keep + __shfl_xor_sync(~0u, send, 4);
  }
  d += __shfl_xor_sync(~0u, d, 2);
  int col = (lane & 1) * 8 + (b4 ? 4 : 0) + (b3 ? 2 : 0) + (b2 ? 1 : 0);
  if (!(lane & 2)) sts32(red_w + col * 4, __float_as_uint(d));
}
template <int NW>
DEVI void gemv_final(uint32_t red, int grp, int lane, uint32_t tag) {
  if (lane < 8) {
    float s0 = 0.f, s1 = 0.f;
#pragma unroll
    for (int w = 0; w < NW; w++) {
      uint2 v = lds64(red + w * 64 + lane * 8);
      s0 += __uint_as_float(v.x);
      s1 += __uint_as_float(v.y);
    }
    ll_store(&g_mod[grp * 8 + lane], pack2(s0, s1), tag);
  }
}

DEVI void stage_to_global(uint32_t p0, uint32_t p1, bf16* dst, int lane) {
#pragma unroll
  for (int m = 0; m < 4; m++) {
    int row = m * 4 + (lane >> 3), ch = lane & 7;
    uint4 v = lds128(p0 + row * 128 + ((ch ^ (row & 7)) << 4));
    stg128(dst + row * DM + ch * 8, v);
  }
  int row = lane >> 1, ch = lane & 1;
  uint4 v = lds128(p1 + row * 32 + ch * 16);
  stg128(dst + row * DM + 64 + ch * 8, v);
}

DEVI bool reduce_valid(const uint4 (&v)[4], uint32_t ep1) {
  uint32_t a = ~0u, o = 0u;
#pragma unroll
  for (int jj = 0; jj < 4; jj++) {
    a &= v[jj].x & v[jj].y & v[jj].z & v[jj].w;
    o |= v[jj].x | v[jj].y | v[jj].z | v[jj].w;
  }
  return __all_sync(~0u, ((ep1 & 1u) ? a : ~o) & 1u);
}
DEVI void reduce_load(const Params& p, int row, int col, uint4 (&v)[4], uint4& xv, uint4& bv) {
  const size_t off = ((size_t)row * DM + col) / 8;
#pragma unroll
  for (int jj = 0; jj < 4; jj++) v[jj] = ll_load16(&g_part[(size_t)jj * (SEQ * DM / 8) + off]);
  xv = ldg_cg(&g_x1[off]);
  bv = ldg_nc(p.b2 + col);
}
DEVI void reduce_finish(const Params& p, uint32_t sb, int row, int col, const uint4 (&v)[4], uint4 xv, uint4 bv) {
  const uint4 gv = lds128(sb + OFF_GB + col * 2);
  float a[8];
  a[0] = bf_lo(bv.x); a[1] = bf_hi(bv.x); a[2] = bf_lo(bv.y); a[3] = bf_hi(bv.y);
  a[4] = bf_lo(bv.z); a[5] = bf_hi(bv.z); a[6] = bf_lo(bv.w); a[7] = bf_hi(bv.w);
#pragma unroll
  for (int jj = 0; jj < 4; jj++) {
    a[0] += bf_lo(v[jj].x); a[1] += bf_hi(v[jj].x); a[2] += bf_lo(v[jj].y); a[3] += bf_hi(v[jj].y);
    a[4] += bf_lo(v[jj].z); a[5] += bf_hi(v[jj].z); a[6] += bf_lo(v[jj].w); a[7] += bf_hi(v[jj].w);
  }
  uint4 o;
  o.x = pack2(fmaf(a[0], bf_lo(gv.x), bf_lo(xv.x)), fmaf(a[1], bf_hi(gv.x), bf_hi(xv.x)));
  o.y = pack2(fmaf(a[2], bf_lo(gv.y), bf_lo(xv.y)), fmaf(a[3], bf_hi(gv.y), bf_hi(xv.y)));
  o.z = pack2(fmaf(a[4], bf_lo(gv.z), bf_lo(xv.z)), fmaf(a[5], bf_hi(gv.z), bf_hi(xv.z)));
  o.w = pack2(fmaf(a[6], bf_lo(gv.w), bf_lo(xv.w)), fmaf(a[7], bf_hi(gv.w), bf_hi(xv.w)));
  stg128(p.out + (size_t)row * DM + col, o);
}

template <int H>
DEVI void qk_issue(float (&S)[32], const uint32_t (&qm)[4][2][4], uint32_t kv) {
  WG_FENCE();
  wgmma_rz_n64_t0(S, qm[H][0], mkdesc(kv, H * 256, KV_ATOM, 3));
  wgmma_rs_n64_t0(S, qm[H][1], mkdesc(kv, (H + 1) * 256, KV_ATOM, 3), 1);
  WG_COMMIT();
}
template <int H>
DEVI void pv_issue(float (&O)[12], const uint32_t (&P)[4][4], uint32_t kv) {
  WG_FENCE();
#pragma unroll
  for (int u = 0; u < 4; u++) wgmma_rs_n24_t1(O, P[u], mkdesc(kv, 1280 + H * 384 + u * 2 * KV_ATOM, 128, 0), 1);
  WG_COMMIT();
}
DEVI void exp_group(const float* S, uint32_t (&P)[4], const uint32_t (&m)[3]) {
  P[0] = pack2(ex2p(S[0]), ex2v(S[1])) & m[0];
  P[1] = pack2(ex2v(S[2]), ex2v(S[3])) & m[1];
  P[2] = pack2(ex2p(S[4]), ex2v(S[5])) & m[2];
  P[3] = pack2(ex2v(S[6]), ex2v(S[7])) & m[0];
}
template <int H, int U>
DEVI void pv_step(float (&O)[12], const uint32_t (&P)[4], uint32_t kv) {
  WG_FENCE();
  wgmma_rs_n24_t1(O, P, mkdesc(kv, 1280 + H * 384 + U * 2 * KV_ATOM, 128, 0), 1);
}
template <int H>
DEVI void att_head(float (&O)[4][12], const float (&S)[32], float (&Sn)[32], uint32_t (&P)[4][4], const uint32_t (&qm)[4][2][4],
                   uint32_t kv, const uint32_t (&m)[4][3]) {
  exp_group(&S[0], P[0], m[0]);
  if constexpr (H > 0) {
    pv_step<H - 1, 3>(O[H - 1], P[3], kv);
    WG_COMMIT();
  }
  if constexpr (H < 3) qk_issue<H + 1>(Sn, qm, kv);
  if constexpr (H > 0) WG_WAIT(H < 3 ? 2 : 1);
  exp_group(&S[8], P[1], m[1]);
  pv_step<H, 0>(O[H], P[0], kv);
  exp_group(&S[16], P[2], m[2]);
  pv_step<H, 1>(O[H], P[1], kv);
  WG_COMMIT();
  if constexpr (H > 0) WG_WAIT(H < 3 ? 2 : 1);
  exp_group(&S[24], P[3], m[3]);
  pv_step<H, 2>(O[H], P[2], kv);
  WG_COMMIT();
  if constexpr (H < 3) WG_WAIT(1);
}
DEVI void att_fast_piece(float (&O)[4][12], const uint32_t (&qm)[4][2][4], uint32_t kv, const uint32_t (&m)[4][3]) {
  float S0[32], S1[32];
  uint32_t P[4][4];
  qk_issue<0>(S0, qm, kv);
  WG_WAIT(0);
  att_head<0>(O, S0, S1, P, qm, kv, m);
  att_head<1>(O, S1, S0, P, qm, kv, m);
  att_head<2>(O, S0, S1, P, qm, kv, m);
  att_head<3>(O, S1, S0, P, qm, kv, m);
  pv_step<3, 3>(O[3], P[3], kv);
  WG_COMMIT();
  WG_WAIT(0);
}
DEVI void softmax_slab(float (&S)[32], uint32_t (&P)[4][4], float (&O)[12], float& m0, float& m1, int lo, int hi,
                       int pu, bool k0, bool k1, bool diag) {
  const float NEG = __int_as_float(0xff800000);
  float x0 = m0, x1 = m1;
#pragma unroll
  for (int u = 0; u < 4; u++) {
    if (u == pu) {
      S[8 * u + 0] = k0 ? S[8 * u + 0] : NEG;
      S[8 * u + 1] = k1 ? S[8 * u + 1] : NEG;
      S[8 * u + 2] = diag ? S[8 * u + 2] : NEG;
      S[8 * u + 3] = diag ? S[8 * u + 3] : NEG;
      S[8 * u + 4] = diag ? NEG : S[8 * u + 4];
      S[8 * u + 5] = diag ? NEG : S[8 * u + 5];
      S[8 * u + 6] = k0 ? S[8 * u + 6] : NEG;
      S[8 * u + 7] = k1 ? S[8 * u + 7] : NEG;
    }
    if (u >= lo && u <= hi) {
      x0 = fmaxf(x0, fmaxf(fmaxf(S[8 * u + 0], S[8 * u + 1]), fmaxf(S[8 * u + 4], S[8 * u + 5])));
      x1 = fmaxf(x1, fmaxf(fmaxf(S[8 * u + 2], S[8 * u + 3]), fmaxf(S[8 * u + 6], S[8 * u + 7])));
    }
  }
  x0 = fmaxf(x0, __shfl_xor_sync(~0u, x0, 1));
  x1 = fmaxf(x1, __shfl_xor_sync(~0u, x1, 1));
  x0 = fmaxf(x0, __shfl_xor_sync(~0u, x0, 2));
  x1 = fmaxf(x1, __shfl_xor_sync(~0u, x1, 2));
  {
    float a0 = ex2(m0 - x0), a1 = ex2(m1 - x1);
#pragma unroll
    for (int t = 0; t < 3; t++) {
      O[4 * t + 0] *= a0; O[4 * t + 1] *= a0;
      O[4 * t + 2] *= a1; O[4 * t + 3] *= a1;
    }
  }
  m0 = x0; m1 = x1;
#pragma unroll
  for (int u = 0; u < 4; u++) {
    if (u >= lo && u <= hi) {
      P[u][0] = pack2(ex2(S[8 * u + 0] - x0), ex2(S[8 * u + 1] - x0));
      P[u][1] = pack2(ex2(S[8 * u + 2] - x1), ex2(S[8 * u + 3] - x1));
      P[u][2] = pack2(ex2(S[8 * u + 4] - x0), ex2(S[8 * u + 5] - x0));
      P[u][3] = pack2(ex2(S[8 * u + 6] - x1), ex2(S[8 * u + 7] - x1));
    } else {
      P[u][0] = P[u][1] = P[u][2] = P[u][3] = 0u;
    }
  }
}

DEVI void att_norm(const float (&O)[12], uint32_t* res, int lane) {
  const float l0 = __shfl_sync(~0u, O[8], (lane & ~3) | 2), l1 = __shfl_sync(~0u, O[10], (lane & ~3) | 2);
  const float i0 = __fdividef(1.0f, l0), i1 = __fdividef(1.0f, l1);
#pragma unroll
  for (int t = 0; t < 3; t++) {
    res[2 * t] = pack2(O[4 * t] * i0, O[4 * t + 1] * i0);
    res[2 * t + 1] = pack2(O[4 * t + 2] * i1, O[4 * t + 3] * i1);
  }
}

DEVI int g2_atom(int s, int half, int r) {
  const bool own = half ? s > 0 : s == 4;
  const int k = half ? (s == 0 ? 1 : s == 4 ? 4 : s - 1) : (s == 0 ? 0 : s == 4 ? 3 : s + 1);
  return 2 * k + (own ? r : r ^ 1);
}
template <int S>
DEVI void g2_step(float (&acc)[64], const uint32_t (&h)[14][4], uint32_t sa, uint32_t sb) {
  if constexpr (S == 0) wgmma_rz_n128_t1(acc, h[S], mkdesc(sa, 0, 1024, 1));
  else if constexpr (S < 7) wgmma_rs_n128_t1(acc, h[S], mkdesc(sa, S * 2048, 1024, 1), 1);
  else if constexpr (S < 12) wgmma_rs_n128_t1(acc, h[S], mkdesc(sb, (S - 7) * 2048, 1024, 1), 1);
  else wgmma_rs_n128_t1(acc, h[S], mkdesc(sb - ((10240 - 4096) << 12), 20480 + (S - 12) * 2048, 1024, 1), 1);
}
template <int S0, int S1>
DEVI void g2_steps(float (&acc)[64], const uint32_t (&h)[14][4], uint32_t sa, uint32_t sb) {
  if constexpr (S0 < S1) {
    g2_step<S0>(acc, h, sa, sb);
    g2_steps<S0 + 1, S1>(acc, h, sa, sb);
  }
}
struct G2Ctx { uint32_t sb, peer, par; int wg, tw, srow, lane; };

DEVI void g2_fetch(uint4 (&v)[4], const G2Ctx& c, int k) {
#pragma unroll
  for (int u = 0; u < 4; u++) v[u] = lds128(c.sb + OFF_A + (k & 3) * 16384 + c.wg * 8192 + u * 2048 + c.tw * 16);
}
DEVI void g2_add(uint32_t* w, const uint4 (&v)[4], uint32_t par) {
  const uint32_t one = 0x3f803f80u;
#pragma unroll
  for (int u = 0; u < 4; u++) {
    w[4 * u + 0] = (hfma2(w[4 * u + 0], one, v[u].x) & ~1u) | par;
    w[4 * u + 1] = (hfma2(w[4 * u + 1], one, v[u].y) & ~1u) | par;
    w[4 * u + 2] = (hfma2(w[4 * u + 2], one, v[u].z) & ~1u) | par;
    w[4 * u + 3] = (hfma2(w[4 * u + 3], one, v[u].w) & ~1u) | par;
  }
}
DEVI uint32_t g2_stg(int k, int wg) { return (k == 3 ? OFF_A + 16384 : OFF_B + 5 * SLOT_B) + wg * 8192; }
DEVI void g2_stage(const uint32_t* w, const G2Ctx& c, int k) {
  const uint32_t st = c.sb + g2_stg(k, c.wg) + c.srow * 128;
#pragma unroll
  for (int u = 0; u < 4; u++)
    stsm4(st + (((2 * u + (c.lane >> 4)) ^ (c.srow & 7)) << 4), w[4 * u], w[4 * u + 1], w[4 * u + 2], w[4 * u + 3]);
}
DEVI void g2_send(const uint32_t* w, const G2Ctx& c, int k) {
#pragma unroll
  for (int u = 0; u < 4; u++)
    asm volatile("st.async.weak.shared::cluster.mbarrier::complete_tx::bytes.v4.b32 [%0], {%1,%2,%3,%4}, [%5];"
                 ::"r"(c.peer + OFF_A + (k & 3) * 16384 + c.wg * 8192 + u * 2048 + c.tw * 16), "r"(w[4 * u]), "r"(w[4 * u + 1]),
                 "r"(w[4 * u + 2]), "r"(w[4 * u + 3]), "r"(c.peer + OFF_BAR + 8 * (B_RX + 2 * k + c.wg)) : "memory");
}
DEVI void g2_emit(uint32_t (&w)[32], const G2Ctx& c, int s) {
  if (s > 0) {
    const int kh = s == 4 ? 4 : s - 1;
    uint4 v[4];
    g2_fetch(v, c, kh);
    g2_add(&w[16], v, c.par);
    g2_stage(&w[16], c, kh);
    if (s == 4) {
      g2_fetch(v, c, 3);
      g2_add(&w[0], v, c.par);
      g2_stage(&w[0], c, 3);
    }
    fence_async_smem();
    __syncwarp();
    if (c.lane == 0) mbar_arrive(c.sb + OFF_BAR + 8 * (B_SF + 2 * s + c.wg));
  }
  if (s < 4) g2_send(&w[0], c, s == 0 ? 0 : s + 1);
  if (s == 0) g2_send(&w[16], c, 1);
}

__global__ void __launch_bounds__(384, 1)
fused_block_kernel(const __grid_constant__ TMaps tm, const Params p) {
  extern __shared__ __align__(1024) uint8_t smem_raw[];
  const uint32_t sb = s2u(smem_raw);
  const int tid = threadIdx.x;
  const int lane = tid & 31;
  const int wid = __shfl_sync(~0u, tid >> 5, 0);

  uint32_t rank;
  asm volatile("mov.u32 %0, %%cluster_ctarank;" : "=r"(rank));
  int item;
  if (p.use_smid) {
    uint32_t smid;
    asm volatile("mov.u32 %0, %%smid;" : "=r"(smid));
    const int t = smid >> 1;
    int g, c;
    if (t < 32) { g = t & 7; c = t >> 3; }
    else if (t < 60) { g = 1 + (t - 32) % 7; c = 4 + (t - 32) / 7; }
    else if (t < 62) { g = -1; c = 0; }
    else { g = 0; c = 4 + (t - 62); }
    item = g < 0 ? -1 : (2 * g + (c & 1)) * 8 + (c >> 1) * 2 + (int)rank;
  } else {
    item = blockIdx.x < 128 ? (int)blockIdx.x : -1;
  }
  item = __shfl_sync(~0u, item, 0);
  if (item < 0) {
    if (tid == 0) {
      unsigned long long tk = atomicAdd(&g_ticket, 1ull);
      unsigned long long goal = (tk / NCTA + 1) * NCTA, v;
      int it = 0;
      do {
        asm volatile("ld.relaxed.gpu.global.u64 %0, [%1];" : "=l"(v) : "l"(&g_ticket) : "memory");
      } while (v < goal && ++it < SPIN_LIMIT);
    }
    return;
  }
  const int bi = item >> 3, bj = item & 7;
  const uint32_t bar = sb + OFF_BAR;
#define BAR(i) (bar + 8 * (i))
  const int f_main = bj < 6 ? 224 * bj + ((bj & 1) ? 32 : 0) : 1344 + 192 * (bj - 6);
  const int f_rem = bj < 6 ? ((bj & 1) ? 224 * bj : 224 * bj + 192) : 0;

  const int grp1 = item < 80 ? item : -1;

  if (wid >= 8) {
    asm volatile("setmaxnreg.dec.sync.aligned.u32 72;");
    const int pw = wid & 3;
    if (pw == 0) {
      if (lane == 0) { PSTAMP(32); GSTAMP(126); }
      if (lane == 0) {
        mbar_init(BAR(B_SLAB), 1);
        PSTAMP(58);
        if (grp1 >= 0) {
          mbar_expect(BAR(B_SLAB), 20480);
#pragma unroll 1
          for (int m = 0; m < 4; m++) tma2(sb + OFF_SLAB + m * 5120, &tm.wmod, BAR(B_SLAB), grp1 * 16, m * 160);
        }
        PSTAMP(59);
#pragma unroll 1
        for (int i = 0; i < 4; i++) mbar_init(BAR(B_FULL1 + i), 1);
        mbar_init(BAR(B_SLABFREE), 8);
        asm volatile("fence.mbarrier_init.release.cluster;" ::: "memory");
      }
      __syncwarp();
      bar_arrive(NB_SETUP, 384);
      if (lane == 0) {
#pragma unroll 1
        for (int kb = 0; kb < 10; kb++) {
          const int s = kb & 3;
          if (kb == 2) mbar_wait(BAR(B_SLABFREE), 0);
          if (kb == 4 && item >= 96) {
            mbar_expect(BAR(B_SLAB2), 20480);
#pragma unroll 1
            for (int m = 0; m < 4; m++) tma2(sb + OFF_SLAB + m * 5120, &tm.wmod, BAR(B_SLAB2), (112 + item) * 16, m * 160);
          }
          if (kb >= 4) mbar_wait(BAR(B_EMPTY1 + s), ((kb >> 2) - 1) & 1);
          const uint32_t fb = BAR(B_FULL1 + s), bs = sb + OFF_B + s * SLOT_B1;
          mbar_expect(fb, 16384 + SLOT_B1);
          tma2(sb + OFF_A + s * 16384, &tm.x, fb, kb * 64, bi * 128);
          tma3(bs, &tm.wqkv_m, fb, bj * 80, kb * 64, 0);
          tma3(bs + 24576, &tm.wqkv_r, fb, bj * 80 + 64, kb * 64, 0);
        }
        PSTAMP(44);
        l2_prefetch((const char*)p.wo + item * 6400, 6400);
        l2_prefetch((const char*)p.w1 + item * 17280, 17280);
        l2_prefetch((const char*)p.w2 + item * 17280, 17280);
        if (item >= 96) mbar_wait(BAR(B_SLAB2FREE), 0);
        mbar_expect(BAR(B_SLAB2), 20480);
#pragma unroll 1
        for (int m = 0; m < 4; m++) tma2(sb + OFF_SLAB + m * 5120, &tm.wmod, BAR(B_SLAB2), (80 + item) * 16, m * 160);
        mbar_wait(BAR(B_QKVDONE), 0);
        const uint32_t ep1 = lds32(sb + OFF_EP);
        PSTAMP(33);
#pragma unroll 1
        for (int t = 3; t >= 0; t--) {
          const int d = 2 - (t >> 1);
          if (bi >= d) {
            const int src = (item - 8 * d) * 2 + (t & 1);
            poll_ge(&g_flag_kv[src * 8], ep1);
            mbar_expect(BAR(B_KV + t), KV_HALF);
            bulk_load(sb + d * KV_IMG + (t & 1) * KV_HALF, &g_kv[(size_t)src * (KV_HALF / 16)], KV_HALF, BAR(B_KV + t));
          }
        }
        PSTAMP(34);
        mbar_wait(BAR(B_SLAB2FREE), item >= 96);
        mbar_expect(BAR(B_WOB), 8 * 10240);
#pragma unroll 1
        for (int n = 0; n < 8; n++) tma3(sb + OFF_WO + (9 - n) * 10240, &tm.wo, BAR(B_WOB), 0, n * 64, bj * 5);
        mbar_wait(BAR(B_ATTDONE), 0);
        PSTAMP(35);
        int m = 0;
#pragma unroll 1
        for (int n = 0; n < 30; n++) {
          if (n == 0 || n == 10) {
            poll_ge(n ? &g_flag_x1[bi * 32] : &g_flag_o[bi * 32], ep1 * 8);
            fence_async_gmem();
            PSTAMP(n ? 38 : 36);
          }
          if (n < 20) {
            const int s = n & 3;
            if (n >= 4) mbar_wait(BAR(B_AE + s), ((n >> 2) - 1) & 1);
            mbar_expect(BAR(B_AF + s), 16384);
            tma2(sb + OFF_A + s * 16384, n < 10 ? &tm.o : &tm.x1, BAR(B_AF + s), (n < 10 ? n : n - 10) * 64, bi * 128);
          }
          if (n == 3) {
            mbar_expect(BAR(B_WOB + 1), 2 * 10240);
            tma3(sb + OFF_WO, &tm.wo, BAR(B_WOB + 1), 0, 8 * 64, bj * 5);
            tma3(sb + OFF_WO + 10240, &tm.wo, BAR(B_WOB + 1), 0, 9 * 64, bj * 5);
          }
          const int mend = n < 5 ? 0 : n < 7 ? n - 4 : n < 9 ? 2 : n < 13 ? 4 : n - 8;
#pragma unroll 1
          for (; m < mend && m < 20; m++) {
            const int s = m % 5;
            if (m == 3) mbar_wait(BAR(B_AE + 3), 1);
            if (m >= 5) mbar_wait(BAR(B_BE + s), (m / 5 - 1) & 1);
            const uint32_t fb = BAR(B_BF + s), bs = sb + slot_b(s);
            mbar_expect(fb, SLOT_B);
            if (m < 10) {
              tma3(bs, &tm.w1_m, fb, 0, m * 64, f_main >> 6);
              tma2(bs + 24576, &tm.w1_r, fb, f_rem, m * 64);
            } else {
#pragma unroll 1
              for (int hf = 0; hf < 2; hf++) {
                const int col = g2_atom((m - 10) >> 1, hf, bj & 1) * 64;
                tma2(bs + hf * ((m & 1) ? 10240 : 14336), (m & 1) ? &tm.w2_b : &tm.w2_a, fb, col, f_main + (m & 1) * 112);
                if (m & 1) tma2(bs + 20480 + hf * 4096, &tm.w2_r, fb, col, f_rem);
              }
            }
          }
        }
        GSTAMP(124);
        PSTAMP(39);
      }
    } else {
      const int t = tid - 288;
      if (t == 0) {
        unsigned long long tk = atomicAdd(&g_ticket, 1ull);
        init_barriers(bar, 8);
        sts32(sb + OFF_EP, (uint32_t)(tk / NCTA) + 1u);
      } else if (lane == 0) {
        init_barriers(bar, 7 + pw);
      }
      __syncwarp();
      bar_sync(NB_SETUP, 384);
      const uint32_t ep1 = lds32(sb + OFF_EP);
      if (pw == 1) {
        if (lane == 0) {
          mbar_wait(BAR(B_KV + 5), 0);
          PSTAMP(40);
          bulk_store(&g_kv[(size_t)(item * 2 + 1) * (KV_HALF / 16)], sb + KV_HALF, KV_HALF);
          bulk_commit();
          mbar_wait(BAR(B_KV + 4), 0);
          bulk_store(&g_kv[(size_t)(item * 2) * (KV_HALF / 16)], sb, KV_HALF);
          bulk_commit();
          bulk_wait1();
          red_release(&g_flag_kv[(item * 2 + 1) * 8]);
          PSTAMP(41);
          bulk_wait0();
          red_release(&g_flag_kv[(item * 2) * 8]);
          PSTAMP(43);
#pragma unroll 1
          for (int k = 0; k < 2; k++) {
            mbar_wait(BAR(B_OPUB + k), 0);
            PSTAMP(48 + 2 * k);
            red_release(k ? &g_flag_x1[bi * 32] : &g_flag_o[bi * 32]);
            PSTAMP(49 + 2 * k);
          }
#pragma unroll 1
          for (int n = 2; n < 10; n++) {
            const int st = n >> 1, wq = n & 1;
            mbar_wait(BAR(B_SF + n), 0);
#pragma unroll 1
            for (int k = st == 4 ? 3 : st - 1; k < st + (st == 4); k++)
              tma2_store(&tm.part, sb + g2_stg(k, wq), (2 * k + (bj & 1)) * 64, (bj >> 1) * SEQ + bi * 128 + wq * 64);
            bulk_commit();
            if (st <= 3) { bulk_wait0(); mbar_arrive(BAR(B_SE + n - 2)); }
          }
          bulk_wait0();
        }
      } else {
        const int t2 = t - 32;
#pragma unroll 1
        for (int r = t2; r < 640; r += 64) sts32(sb + OFF_C + r * 4, __float_as_uint(silu_bf(__bfloat162float(p.c[r]))));
        bar_sync(NB_P23, 64);
#pragma unroll 1
        for (int k = 0; k < (item >= 96 ? 2 : 1); k++) {
          mbar_wait(BAR(B_SLAB2), k);
          float a[8] = {0.f, 0.f, 0.f, 0.f, 0.f, 0.f, 0.f, 0.f};
#pragma unroll 2
          for (int r = t2; r < 1280; r += 64) {
            const uint4 wv = lds128(sb + OFF_SLAB + r * 16);
            const float s = __uint_as_float(lds32(sb + OFF_C + (r >> 1) * 4));
            a[0] = fmaf(s, bf_lo(wv.x), a[0]); a[1] = fmaf(s, bf_hi(wv.x), a[1]);
            a[2] = fmaf(s, bf_lo(wv.y), a[2]); a[3] = fmaf(s, bf_hi(wv.y), a[3]);
            a[4] = fmaf(s, bf_lo(wv.z), a[4]); a[5] = fmaf(s, bf_hi(wv.z), a[5]);
            a[6] = fmaf(s, bf_lo(wv.w), a[6]); a[7] = fmaf(s, bf_hi(wv.w), a[7]);
          }
          if (k) bar_sync(NB_P23, 64);
          gemv_partial(a, lane, sb + OFF_RED + 512 + (pw - 2) * 64);
          if (lane == 0) mbar_arrive(BAR(B_SLAB2FREE));
          __syncwarp();
          bar_sync(NB_P23, 64);
          if (pw == 2) gemv_final<2>(sb + OFF_RED + 512, 80 + item + ((item >= 96 && k == 0) ? 32 : 0), lane, ep1);
          __syncwarp();
        }
#pragma unroll
        for (int k = 0; k < 4; k++) {
          const int u = t2 + 64 * k;
          if (u < 224) {
            const float v = u < 192 ? __bfloat162float(p.b1[f_main + u]) : (bj < 6 ? __bfloat162float(p.b1[f_rem + u - 192]) : 0.f);
            sts32(sb + OFF_B1T + u * 4, __float_as_uint(0.5f * v));
          }
        }
        mbar_wait(BAR(B_QKVDONE), 0);
        float g1 = 0.f, g2 = 0.f, gs = 0.f, s1 = 0.f, s2 = 0.f;
#pragma unroll 1
        for (int u = t2; u < 160; u += 64) {
          unsigned long long w[7];
          int it = 0;
          bool ok;
          do {
            asm volatile("ld.relaxed.gpu.global.v2.u64 {%0, %1}, [%2];" : "=l"(w[0]), "=l"(w[1]) : "l"(&g_mod[1280 + 2 * u]) : "memory");
            asm volatile("ld.relaxed.gpu.global.v2.u64 {%0, %1}, [%2];" : "=l"(w[2]), "=l"(w[3]) : "l"(&g_mod[960 + 2 * u]) : "memory");
            asm volatile("ld.relaxed.gpu.global.v2.u64 {%0, %1}, [%2];" : "=l"(w[4]), "=l"(w[5]) : "l"(&g_mod[1600 + 2 * u]) : "memory");
            asm volatile("ld.relaxed.gpu.global.u64 %0, [%1];" : "=l"(w[6]) : "l"(&g_mod[640 + 40 * bj + (u < 40 ? u : 0)]) : "memory");
            ok = true;
#pragma unroll
            for (int e = 0; e < 7; e++) ok = ok && (uint32_t)(w[e] >> 32) == ep1;
            if (!ok) __nanosleep(200);
          } while (!ok && ++it < SPIN_LIMIT);
          const uint32_t one = 0x3f803f80u, sx = (uint32_t)w[2], sy = (uint32_t)w[3];
          const uint32_t ga_ = hfma2((uint32_t)w[0], one, one), gb_ = hfma2((uint32_t)w[1], one, one);
          const int pp = (2 * u) & 7;
          const uint32_t a = sb + OFF_TAB + (u >> 2) * 64 + (pp & 3) * 16 + (pp >> 2) * 8;
          sts64(a, ga_, sx);
          sts64(a + 16, gb_, sy);
          sts64(sb + OFF_GB + u * 8, (uint32_t)w[4], (uint32_t)w[5]);
          if (u < 40) sts64(sb + OFF_GA + (u >> 3) * 64 + (u & 3) * 16 + ((u >> 2) & 1) * 8, (uint32_t)w[6] << 16, (uint32_t)w[6] & 0xffff0000u);
          const float gg[4] = {bf_lo(ga_), bf_hi(ga_), bf_lo(gb_), bf_hi(gb_)};
          const float ss[4] = {bf_lo(sx), bf_hi(sx), bf_lo(sy), bf_hi(sy)};
#pragma unroll
          for (int e = 0; e < 4; e++) {
            g1 += gg[e]; g2 = fmaf(gg[e], gg[e], g2); gs = fmaf(gg[e], ss[e], gs);
            s1 += ss[e]; s2 = fmaf(ss[e], ss[e], s2);
          }
        }
#pragma unroll
        for (int o = 16; o > 0; o >>= 1) {
          g1 += __shfl_xor_sync(~0u, g1, o); g2 += __shfl_xor_sync(~0u, g2, o); gs += __shfl_xor_sync(~0u, gs, o);
          s1 += __shfl_xor_sync(~0u, s1, o); s2 += __shfl_xor_sync(~0u, s2, o);
        }
        if (lane == 0) {
          const uint32_t a = sb + OFF_CST + (pw - 2) * 32;
          sts32(a, __float_as_uint(g1)); sts32(a + 4, __float_as_uint(g2)); sts32(a + 8, __float_as_uint(gs));
          sts32(a + 12, __float_as_uint(s1)); sts32(a + 16, __float_as_uint(s2));
        }
        __syncwarp();
        mbar_arrive(BAR(B_TAB2));
        if (t2 == 0) PSTAMP(62);
        if (pw == 2) {
          mbar_wait(BAR(B_TAB2), 0);
          mbar_wait(BAR(B_SPUB), 0);
          const int row = bj * 16 + (lane & 15), hf = lane >> 4;
          uint4 v[8];
          int it = 0;
          bool ok;
          do {
            ok = true;
#pragma unroll
            for (int e = 0; e < 8; e++) {
              v[e] = ll_load16(&g_stats[((bi * 8 + e) * 2 + hf) * 128 + row]);
              ok = ok && v[e].w == ep1;
            }
          } while (!ok && ++it < SPIN_LIMIT);
          __syncwarp();
          float sv[6];
          sv[0] = sv[1] = sv[2] = 0.f;
#pragma unroll
          for (int e = 0; e < 8; e++) {
            sv[0] += __uint_as_float(v[e].x); sv[1] += __uint_as_float(v[e].y); sv[2] += __uint_as_float(v[e].z);
          }
#pragma unroll
          for (int e = 0; e < 3; e++) sv[3 + e] = __shfl_down_sync(~0u, sv[e], 16);
          float cst[5];
#pragma unroll
          for (int e = 0; e < 5; e++) cst[e] = __uint_as_float(lds32(sb + OFF_CST + e * 4)) + __uint_as_float(lds32(sb + OFF_CST + 32 + e * 4));
          const float inv = 1.0f / DM;
          const float mu1 = sv[0] * inv;
          const float r1 = rsqrtf(fmaxf(fmaf(-mu1, mu1, sv[1] * inv), 0.f) + 1e-5f);
          const float mu2 = fmaf(r1, fmaf(-mu1, cst[0], sv[2]), cst[3]) * inv;
          const float hh = fmaf(r1 * r1, fmaf(mu1, fmaf(mu1, cst[1], -2.f * sv[3]), sv[4]),
                                fmaf(2.f * r1, fmaf(-mu1, cst[2], sv[5]), cst[4])) * inv;
          const float r2 = 0.5f * rsqrtf(fmaxf(fmaf(-mu2, mu2, hh), 0.f) + 1e-5f);
          const float ab = bf_lo(pack2(r1 * r2, 0.f) & 0xffffu);
          if (lane < 16)
            ll_store16(&g_fin[bi * 128 + row], __uint_as_float(pack2(ab, -mu1 * ab)), __uint_as_float(pack2(r2, -mu2 * r2)), 0.f, ep1);
          __syncwarp();
          if (lane == 0) { mbar_arrive(BAR(B_FIN)); PSTAMP(55); }
        }
        if (pw == 3) {
          if (lane < 10) mbar_expect(BAR(B_RX + lane), 8192);
#pragma unroll 1
          for (int k = 0; k < 5; k++) {
            const int col = (2 * k + (bj & 1)) * 64, row = bi * 128 + (bj >> 1) * 32;
            mbar_wait(BAR(B_SF + 2 * (k < 3 ? k + 1 : 4) + (bj >> 2)), 0);
            const uint4* hp = &g_part[(size_t)(lane & 3) * (SEQ * DM / 8) + ((size_t)(row + 31) * DM + col + 56) / 8];
            int it = 0;
            while (!__all_sync(~0u, ((ll_load16(hp).w ^ ep1) & 1u) == 0u) && ++it < SPIN_LIMIT) {}
            if (lane == 0) { PSTAMP(74 + k); mbar_arrive(BAR(B_RF + k)); }
            __syncwarp();
          }
        }
      }
    }
  } else {
    asm volatile("setmaxnreg.inc.sync.aligned.u32 216;");
    const int wg = wid >> 2, w = wid & 3, w8 = wid;
    const int g = lane >> 2, q = lane & 3;
    const int wr = wg ? 3 - w : w;
    CSTAMP(0);
    uint32_t ep1;
    uint32_t ra0, rc0, ra1, rc1;
    {
      const int row = bi * 128 + bj * 16 + 2 * w8 + (lane >> 4);
      uint32_t craw[5];
#pragma unroll
      for (int m = 0; m < 5; m++) asm volatile("ld.global.nc.u16 %0, [%1];" : "=r"(craw[m]) : "l"(p.c + (tid >> 1) + 128 * m));
      uint4 xv[5];
#pragma unroll
      for (int m = 0; m < 5; m++) xv[m] = ldg_nc(p.x + (size_t)row * DM + ((lane & 15) + 16 * m) * 8);
      if (lane == 0) init_barriers(bar, w8);
      __syncwarp();
      DSTAMP(53, 0u);
      bar_sync(NB_SETUP, 384);
      if (tid == 0) PSTAMP(45);
      ep1 = lds32(sb + OFF_EP);
      float f[40];
#pragma unroll
      for (int m = 0; m < 5; m++) {
        f[8 * m + 0] = bf_lo(xv[m].x); f[8 * m + 1] = bf_hi(xv[m].x); f[8 * m + 2] = bf_lo(xv[m].y); f[8 * m + 3] = bf_hi(xv[m].y);
        f[8 * m + 4] = bf_lo(xv[m].z); f[8 * m + 5] = bf_hi(xv[m].z); f[8 * m + 6] = bf_lo(xv[m].w); f[8 * m + 7] = bf_hi(xv[m].w);
      }
      float s = 0.f;
#pragma unroll
      for (int e = 0; e < 40; e++) s += f[e];
#pragma unroll
      for (int o = 8; o > 0; o >>= 1) s += __shfl_xor_sync(~0u, s, o);
      const float mean = s * (1.0f / DM);
      float v = 0.f;
#pragma unroll
      for (int e = 0; e < 40; e++) { float d = f[e] - mean; v = fmaf(d, d, v); }
#pragma unroll
      for (int o = 8; o > 0; o >>= 1) v += __shfl_xor_sync(~0u, v, o);
      const float rstd = rsqrtf(v * (1.0f / DM) + 1e-5f);
      const float rb = bf_lo(pack2(rstd, 0.f) & 0xffffu);
      if ((lane & 15) == 0) ll_store(&g_st1[row], pack2(rb, -mean * rb), ep1);
      __syncwarp();
      if (grp1 >= 0) {
        float a[8], sc[5];
#pragma unroll
        for (int m = 0; m < 5; m++) sc[m] = silu_bf(bf_lo(craw[m]));
        mbar_wait(BAR(B_SLAB), 0);
        DSTAMP(54, 0u);
        gemv_acc<256>(sb, tid, sc, a);
        gemv_partial(a, lane, sb + OFF_RED + w8 * 64);
        __syncwarp();
        if (w8 == 0) {
          bar_sync(NB_GEMV, 256);
          gemv_final<8>(sb + OFF_RED, grp1, lane, ep1);
          __syncwarp();
        } else {
          bar_arrive(NB_GEMV, 256);
        }
      }
      CSTAMP(1);
      const int r0 = bi * 128 + wg * 64 + wr * 16 + g;
      const int mu = tid < 160 ? tid : 0;
      unsigned long long v0, v1, c0, c1, s0, s1;
      {
        int it = 0;
        bool ok;
        do {
          asm volatile("ld.relaxed.gpu.global.v2.u64 {%0, %1}, [%2];" : "=l"(c0), "=l"(c1) : "l"(&g_mod[320 + 2 * mu]) : "memory");
          asm volatile("ld.relaxed.gpu.global.v2.u64 {%0, %1}, [%2];" : "=l"(s0), "=l"(s1) : "l"(&g_mod[2 * mu]) : "memory");
          asm volatile("ld.relaxed.gpu.global.u64 %0, [%1];" : "=l"(v0) : "l"(&g_st1[r0]) : "memory");
          asm volatile("ld.relaxed.gpu.global.u64 %0, [%1];" : "=l"(v1) : "l"(&g_st1[r0 + 8]) : "memory");
          ok = (uint32_t)(c0 >> 32) == ep1 && (uint32_t)(c1 >> 32) == ep1 && (uint32_t)(s0 >> 32) == ep1 && (uint32_t)(s1 >> 32) == ep1 &&
               (uint32_t)(v0 >> 32) == ep1 && (uint32_t)(v1 >> 32) == ep1;
        } while (!ok && ++it < SPIN_LIMIT);
      }
      __syncwarp();
      if (lane == 0) mbar_arrive(BAR(B_SLABFREE));
      if (tid < 160) {
        const uint32_t one = 0x3f803f80u;
        const int pp = (2 * tid) & 7;
        const uint32_t a = sb + OFF_TAB + (tid >> 2) * 64 + (pp & 3) * 16 + (pp >> 2) * 8;
        sts64(a, hfma2((uint32_t)c0, one, one), (uint32_t)s0);
        sts64(a + 16, hfma2((uint32_t)c1, one, one), (uint32_t)s1);
      }
      const uint32_t t0 = (uint32_t)v0, t1 = (uint32_t)v1;
      ra0 = __byte_perm(t0, 0, 0x1010); rc0 = __byte_perm(t0, 0, 0x3232);
      ra1 = __byte_perm(t1, 0, 0x1010); rc1 = __byte_perm(t1, 0, 0x3232);
      __syncwarp();
      bar_sync(NB_CONS, 256);
    }
    CSTAMP(2);
    const int arow = wg * 64 + wr * 16 + (lane & 15);
    const uint32_t a_off = arow * 128;
    const int a_hx = lane >> 4, a_rx = arow & 7;
    uint32_t qm[4][2][4];
    {
      float accM[96], accR[24];
      uint32_t af[2][4], raw[2][4];
      uint4 pr[2];
      const uint32_t tab = sb + OFF_TAB + q * 16;
      mbar_wait(BAR(B_FULL1), 0);
#pragma unroll
      for (int kk = 0; kk < 2; kk++) {
        ldsm4(raw[kk], sb + OFF_A + a_off + (((2 * kk + a_hx) ^ a_rx) << 4));
        pr[kk] = lds128(tab + kk * 64);
      }
#pragma unroll 1
      for (int kb = 0; kb < 10; kb++) {
        const int s = kb & 3, sn = (kb + 1) & 3;
        if (tid == 0) PSTAMP(64 + kb);
        const uint32_t bm = dlo(sb + OFF_B + s * SLOT_B1, 8192), br = dlo(sb + OFF_B + s * SLOT_B1 + 24576, 2048);
#pragma unroll
        for (int kk = 0; kk < 4; kk++) {
          const int e = kk & 1;
          af[e][0] = hfma2(hfma2(raw[e][0], ra0, rc0), pr[e].x, pr[e].y);
          af[e][1] = hfma2(hfma2(raw[e][1], ra1, rc1), pr[e].x, pr[e].y);
          af[e][2] = hfma2(hfma2(raw[e][2], ra0, rc0), pr[e].z, pr[e].w);
          af[e][3] = hfma2(hfma2(raw[e][3], ra1, rc1), pr[e].z, pr[e].w);
          WG_FENCE();
          wgmma_rs_n48_t1(accR, af[e], mkdesc(br, kk * 512, 256, 3), (kb | kk) != 0);
          wgmma_rs_n192_t1(accM, af[e], mkdesc(bm, kk * 2048, 1024, 1), (kb | kk) != 0);
          WG_COMMIT();
          if (kk < 2 || kb < 9) {
            if (kk == 2) mbar_wait(BAR(B_FULL1 + sn), ((kb + 1) >> 2) & 1);
            ldsm4(raw[e], sb + OFF_A + (kk < 2 ? s : sn) * 16384 + a_off + (((2 * ((kk + 2) & 3) + a_hx) ^ a_rx) << 4));
            pr[e] = lds128(tab + (kb * 4 + kk + 2) * 64);
          }
          WG_WAIT(1);
          if (kk == 0 && kb > 0 && lane == 0) mbar_arrive(BAR(B_EMPTY1 + ((kb - 1) & 3)));
        }
      }
      WG_WAIT(0);
      CSTAMP(3);
      if (lane == 0) mbar_arrive(BAR(B_QKVDONE));
      __syncwarp();
      bar_sync(NB_CONS, 256);
      {
        const int r = lane & 7;
        const uint32_t ka = sb + (wg * 8 + wr * 2 + ((lane >> 3) & 1)) * KV_ATOM + r * 32 + (((lane >> 4) ^ (r >> 2)) << 4);
#pragma unroll
        for (int u = 0; u < 4; u++)
          stsm4(ka + u * 256, pack2(accM[32 + 8 * u], accM[33 + 8 * u]), pack2(accM[34 + 8 * u], accM[35 + 8 * u]),
                pack2(accM[36 + 8 * u], accM[37 + 8 * u]), pack2(accM[38 + 8 * u], accM[39 + 8 * u]));
        stsm4(ka + 4 * 256, pack2(accR[8], accR[9]), pack2(accR[10], accR[11]), pack2(accR[12], accR[13]), pack2(accR[14], accR[15]));
        const uint32_t va = sb + (wg * 8 + wr * 2) * KV_ATOM + 1280 + g * 16;
#pragma unroll
        for (int t = 0; t < 10; t++) {
          const int cA = 8 * t, cB = 8 * t + 4;
          const int offA = (cA / 20) * 384 + ((cA % 20) >> 3) * 128 + ((cA % 20) & 7) * 2;
          const int offB = (cB / 20) * 384 + ((cB % 20) >> 3) * 128 + ((cB % 20) & 7) * 2;
          const uint32_t a = va + (q < 2 ? offA : offB) + (q & 1) * 4;
          const float* src = t < 8 ? &accM[64 + 4 * t] : &accR[16 + 4 * (t - 8)];
          sts32(a, pack2(src[0], src[1]));
          sts32(a + KV_ATOM, pack2(src[2], src[3]));
        }
        sts64(va + q * 384 + 256 + 8, 0x00003f80u, 0u);
        sts64(va + q * 384 + 256 + 8 + KV_ATOM, 0x00003f80u, 0u);
        fence_async_smem();
        mbar_arrive(BAR(B_KV + 4 + wg));
      }
      {
        const float sc = 0.22360679774997896f * 1.4426950408889634f;
        uint32_t qf[5][4];
#pragma unroll
        for (int u = 0; u < 5; u++) {
          const float* src = u < 4 ? &accM[8 * u] : &accR[0];
#pragma unroll
          for (int e = 0; e < 4; e++) qf[u][e] = pack2(src[2 * e] * sc, src[2 * e + 1] * sc);
        }
#pragma unroll
        for (int h = 0; h < 4; h++)
#pragma unroll
          for (int ks = 0; ks < 2; ks++)
#pragma unroll
            for (int e = 0; e < 4; e++) {
              const int lcA = 16 * ks + (e >> 1) * 8, lcB = lcA + 4;
              const bool vA = lcA >= 4 * h && lcA < 4 * h + 20, vB = lcB >= 4 * h && lcB < 4 * h + 20;
              qm[h][ks][e] = (q < 2 ? vA : vB) ? qf[h + ks][e] : 0u;
              asm volatile("" : "+r"(qm[h][ks][e]));
            }
      }
    }
    CSTAMP(4);
    {
      float O[4][12];
#pragma unroll
      for (int h = 0; h < 4; h++)
#pragma unroll
        for (int e = 0; e < 12; e++) O[h][e] = 0.f;
      const bool p0 = 2 * q <= g, p1 = 2 * q + 1 <= g;
      const uint32_t tri = (p0 ? 0xffffu : 0u) | (p1 ? 0xffff0000u : 0u);
      const int smin = bi >= 2 ? 0 : (bi == 1 ? 2 - wg : 4 - wg);
#pragma unroll 1
      for (int s = 4; s >= smin; s--) {
        const int t = wg + s;
        if (tid == 0) PSTAMP(104 + 2 * (4 - s));
        mbar_wait(BAR(B_KV + t), 0);
        if (tid == 0) PSTAMP(105 + 2 * (4 - s));
        const uint32_t kv = dlo(sb + (2 - (t >> 1)) * KV_IMG + (t & 1) * KV_HALF, KV_ATOM);
        uint32_t m[4][3];
#pragma unroll
        for (int u = 0; u < 4; u++) {
          const uint32_t inv = s == 0 ? ~0u : 0u, edge = (s == 4 || s == 0) ? ~0u : 0u;
          m[u][0] = ((u < wr ? ~0u : u == wr ? tri : 0u) ^ inv) | ~edge;
          m[u][1] = ((u <= wr ? ~0u : 0u) ^ inv) | ~edge;
          m[u][2] = ((u < wr ? ~0u : 0u) ^ inv) | ~edge;
        }
        att_fast_piece(O, qm, kv, m);
      }
      uint32_t redo;
      {
        float z = 0.f;
        bool ok = true;
#pragma unroll
        for (int h = 0; h < 4; h++) {
#pragma unroll
          for (int e = 0; e < 12; e++) z = fmaf(O[h][e], 0.f, z);
          ok = ok && (q != 2 || (O[h][8] >= 8.67e-19f && O[h][10] >= 8.67e-19f));
        }
        ok = ok && z == 0.f;
        asm volatile("{\n.reg .pred p, r;\nsetp.eq.u32 p, %1, 0;\nbar.red.or.pred r, %2, 128, p;\nselp.u32 %0, 1, 0, r;\n}"
                     : "=r"(redo) : "r"((uint32_t)ok), "r"(NB_VOTE + wg) : "memory");
      }
      uint32_t res[24];
      if (redo) {
        uint32_t tmp[24];
#pragma unroll 1
        for (int h = 0; h < 4; h++) {
          uint32_t qh[4][2][4];
#pragma unroll
          for (int e = 0; e < 8; e++) {
            const uint32_t v = h == 0 ? qm[0][e >> 2][e & 3] : h == 1 ? qm[1][e >> 2][e & 3] : h == 2 ? qm[2][e >> 2][e & 3] : qm[3][e >> 2][e & 3];
            qh[0][e >> 2][e & 3] = v;
            asm volatile("" : "+r"(qh[0][e >> 2][e & 3]));
          }
          float O2[12], S0[32], m0 = __int_as_float(0xff800000), m1 = m0;
          uint32_t P0[4][4];
#pragma unroll
          for (int e = 0; e < 12; e++) O2[e] = 0.f;
#pragma unroll 1
          for (int s = 4; s >= smin; s--) {
            const int t = wg + s;
            const uint32_t kv = dlo(sb + (2 - (t >> 1)) * KV_IMG + (t & 1) * KV_HALF, KV_ATOM);
            const bool diag = s == 4;
            qk_issue<0>(S0, qh, kv + h * 16);
            WG_WAIT(0);
            softmax_slab(S0, P0, O2, m0, m1, s == 0 ? wr : 0, diag ? wr : 3, (diag || s == 0) ? wr : -1, p0 == diag, p1 == diag, diag);
            pv_issue<0>(O2, P0, kv + h * 24);
            WG_WAIT(0);
          }
          att_norm(O2, &tmp[6 * h], lane);
        }
#pragma unroll
        for (int e = 0; e < 24; e++) res[e] = tmp[e];
      } else {
#pragma unroll
        for (int h = 0; h < 4; h++) att_norm(O[h], &res[6 * h], lane);
      }
      const uint32_t stg0 = sb + OFF_A + wg * 8192 + wr * 2048, stg1 = stg0 + 16384;
      CSTAMP(5);
      bar_sync(NB_CONS, 256);
      if (lane == 0) mbar_arrive(BAR(B_ATTDONE));
#pragma unroll
      for (int h = 0; h < 4; h++)
#pragma unroll
        for (int t = 0; t < 3; t++) {
          const int c = 20 * h + 8 * t + 2 * q;
          if (t < 2 || q < 2) {
            const uint32_t a0 = c < 64 ? stg0 + g * 128 + (((c >> 3) ^ g) << 4) + (c & 7) * 2 : stg1 + g * 32 + (c - 64) * 2;
            sts32(a0, res[6 * h + 2 * t]);
            sts32(a0 + (c < 64 ? 1024 : 256), res[6 * h + 2 * t + 1]);
          }
        }
      __syncwarp();
      stage_to_global(stg0, stg1, (bf16*)g_o + (size_t)(bi * 128 + wg * 64 + wr * 16) * DM + bj * 80, lane);
      __syncwarp();
      if (lane == 0) mbar_arrive(BAR(B_OPUB));
    }
    CSTAMP(6);
    {
      uint4 xq[5];
      float acc[40];
      mbar_wait(BAR(B_WOB), 0);
      mbar_wait(BAR(B_AF), 0);
      CSTAMP(7);
      {
        const bf16* xs = p.x + (size_t)(bi * 128 + wg * 64 + w * 16) * DM + bj * 80;
#pragma unroll
        for (int m = 0; m < 4; m++) xq[m] = ldg_nc(xs + (m * 4 + (lane >> 3)) * DM + (lane & 7) * 8);
        xq[4] = ldg_nc(xs + (lane >> 1) * DM + 64 + (lane & 1) * 8);
      }
#pragma unroll 1
      for (int n = 0; n < 10; n++) {
        const int s = n & 3, kb = n < 8 ? 9 - n : n - 8;
        if (n == 8) mbar_wait(BAR(B_WOB + 1), 0);
        mbar_wait(BAR(B_AF + s), (n >> 2) & 1);
        const uint32_t as = dlo(sb + OFF_A + s * 16384 + wg * 8192, 16), bs = dlo(sb + OFF_WO + kb * 10240, 2048);
        WG_FENCE();
#pragma unroll
        for (int kk = 0; kk < 4; kk++)
          wgmma_ss_n80_t1(acc, mkdesc(as, kk * 32, 1024, 1), mkdesc(bs, kk * 512, 256, 3), (n | kk) != 0);
        WG_COMMIT();
        WG_WAIT(1);
        if (n > 0 && lane == 0) mbar_arrive(BAR(B_AE + ((n - 1) & 3)));
      }
      const uint32_t stg0 = sb + OFF_A + 32768 + wg * 8192 + w * 2048, stg1 = stg0 + 16384;
      mbar_wait(BAR(B_TAB2), 0);
#pragma unroll
      for (int m = 0; m < 4; m++) {
        const int row = m * 4 + (lane >> 3);
        sts128(stg0 + row * 128 + (((lane & 7) ^ (row & 7)) << 4), xq[m]);
      }
      sts128(stg1 + lane * 16, xq[4]);
      __syncwarp();
      uint32_t xo[5][4];
      uint4 gav[5];
      const int frow = (lane & 7) + ((lane >> 3) & 1) * 8, fdh = lane >> 4;
#pragma unroll
      for (int u = 0; u < 5; u++) {
        ldsm4(xo[u], u < 4 ? stg0 + frow * 128 + (((2 * u + fdh) ^ (frow & 7)) << 4) : stg1 + frow * 32 + fdh * 16);
        gav[u] = lds128(sb + OFF_GA + u * 64 + q * 16);
      }
      WG_WAIT(0);
      CSTAMP(8);
      if (lane == 0) mbar_arrive(BAR(B_AE + 1));
#pragma unroll
      for (int u = 0; u < 5; u++) {
#pragma unroll
        for (int e = 0; e < 4; e++)
          xo[u][e] = pack2(fmaf(__uint_as_float(e < 2 ? gav[u].x : gav[u].z), acc[8 * u + 2 * e], bf_lo(xo[u][e])),
                           fmaf(__uint_as_float(e < 2 ? gav[u].y : gav[u].w), acc[8 * u + 2 * e + 1], bf_hi(xo[u][e])));
        stsm4(u < 4 ? stg0 + frow * 128 + (((2 * u + fdh) ^ (frow & 7)) << 4) : stg1 + frow * 32 + fdh * 16, xo[u][0], xo[u][1], xo[u][2], xo[u][3]);
      }
      __syncwarp();
      stage_to_global(stg0, stg1, (bf16*)g_x1 + (size_t)(bi * 128 + wg * 64 + w * 16) * DM + bj * 80, lane);
      __syncwarp();
      if (lane == 0) mbar_arrive(BAR(B_XPUB));
      if (tid == 0) PSTAMP(52);
      float st[2][6];
#pragma unroll
      for (int e = 0; e < 6; e++) st[0][e] = st[1][e] = 0.f;
#pragma unroll
      for (int t = 0; t < 10; t++) {
        const uint2 gsv = lds64(sb + OFF_TAB + (5 * bj + (t >> 1)) * 64 + q * 16 + (t & 1) * 8);
        const float gl = bf_lo(gsv.x), gh = bf_hi(gsv.x), sl = bf_lo(gsv.y), sh = bf_hi(gsv.y);
#pragma unroll
        for (int r = 0; r < 2; r++) {
          const uint32_t xw = xo[t >> 1][(t & 1) * 2 + r];
          const float a = bf_lo(xw), b = bf_hi(xw), ga = gl * a, gb = gh * b;
          st[r][0] += a + b;
          st[r][1] = fmaf(a, a, fmaf(b, b, st[r][1]));
          st[r][2] += ga + gb;
          st[r][3] = fmaf(gl, ga, fmaf(gh, gb, st[r][3]));
          st[r][4] = fmaf(ga, ga, fmaf(gb, gb, st[r][4]));
          st[r][5] = fmaf(sl, ga, fmaf(sh, gb, st[r][5]));
        }
      }
      {
        const bool hi = q & 1, r1 = q & 2;
        float k6[6], k3[3];
#pragma unroll
        for (int e = 0; e < 6; e++) k6[e] = (r1 ? st[1][e] : st[0][e]) + __shfl_xor_sync(~0u, r1 ? st[0][e] : st[1][e], 2);
#pragma unroll
        for (int e = 0; e < 3; e++) k3[e] = (hi ? k6[3 + e] : k6[e]) + __shfl_xor_sync(~0u, hi ? k6[e] : k6[3 + e], 1);
        ll_store16(&g_stats[(item * 2 + (hi ? 1 : 0)) * 128 + wg * 64 + w * 16 + g + (r1 ? 8 : 0)], k3[0], k3[1], k3[2], ep1);
        __syncwarp();
        if (lane == 0) mbar_arrive(BAR(B_SPUB));
      }
    }
    CSTAMP(9);
    uint32_t hfr[14][4];
    {
      float accM[96], accR[16];
#pragma unroll
      for (int t = 0; t < 28; t++) {
        const uint2 bv = lds64(sb + OFF_B1T + (8 * t + 2 * q) * 4);
        float* d = t < 24 ? &accM[4 * t] : &accR[4 * (t - 24)];
        d[0] = d[2] = __uint_as_float(bv.x);
        d[1] = d[3] = __uint_as_float(bv.y);
        asm volatile("" : "+f"(d[0]), "+f"(d[1]), "+f"(d[2]), "+f"(d[3]));
      }
      uint32_t ka[2], kb_[2], kr[2], kc[2];
      {
        const uint4* fp = &g_fin[bi * 128 + wg * 64 + wr * 16 + g];
        uint4 v0, v1;
        mbar_wait(BAR(B_FIN), 0);
        int it = 0;
        do {
          v0 = ll_load16(fp);
          v1 = ll_load16(fp + 8);
        } while ((v0.w != ep1 || v1.w != ep1) && ++it < SPIN_LIMIT);
        __syncwarp();
        ka[0] = __byte_perm(v0.x, 0, 0x1010); kb_[0] = __byte_perm(v0.x, 0, 0x3232);
        kr[0] = __byte_perm(v0.y, 0, 0x1010); kc[0] = __byte_perm(v0.y, 0, 0x3232);
        ka[1] = __byte_perm(v1.x, 0, 0x1010); kb_[1] = __byte_perm(v1.x, 0, 0x3232);
        kr[1] = __byte_perm(v1.y, 0, 0x1010); kc[1] = __byte_perm(v1.y, 0, 0x3232);
      }
      uint32_t af[2][4], raw[2][4];
      uint4 pr[2];
      const uint32_t tab = sb + OFF_TAB + q * 16;
      DSTAMP(56, ka[0] ^ kc[1]);
      mbar_wait(BAR(B_BF), 0);
      mbar_wait(BAR(B_AF + 2), 0);
      CSTAMP(10);
#pragma unroll
      for (int kk = 0; kk < 2; kk++) {
        ldsm4(raw[kk], sb + OFF_A + 2 * 16384 + a_off + (((2 * kk + a_hx) ^ a_rx) << 4));
        pr[kk] = lds128(tab + kk * 64);
      }
#pragma unroll 1
      for (int kb = 0; kb < 10; kb++) {
        const int n = 10 + kb, s = n & 3, sn = (n + 1) & 3, s5 = kb % 5;
        const uint32_t bs = dlo(sb + slot_b(s5), 8192);
#pragma unroll
        for (int kk = 0; kk < 4; kk++) {
          const int e = kk & 1;
          af[e][0] = hfma2(hfma2(raw[e][0], ka[0], kb_[0]), pr[e].x, hfma2(pr[e].y, kr[0], kc[0]));
          af[e][1] = hfma2(hfma2(raw[e][1], ka[1], kb_[1]), pr[e].x, hfma2(pr[e].y, kr[1], kc[1]));
          af[e][2] = hfma2(hfma2(raw[e][2], ka[0], kb_[0]), pr[e].z, hfma2(pr[e].w, kr[0], kc[0]));
          af[e][3] = hfma2(hfma2(raw[e][3], ka[1], kb_[1]), pr[e].z, hfma2(pr[e].w, kr[1], kc[1]));
          WG_FENCE();
          wgmma_rs_n32_t1(accR, af[e], mkdesc(bs, 24576 + kk * 1024, 512, 2), 1);
          wgmma_rs_n192_t1(accM, af[e], mkdesc(bs, kk * 2048, 1024, 1), 1);
          WG_COMMIT();
          if (kk < 2 || kb < 9) {
            if (kk == 2) {
              mbar_wait2(BAR(B_AF + sn), ((n + 1) >> 2) & 1, BAR(B_BF + (kb + 1) % 5), (kb + 1) / 5);
            }
            ldsm4(raw[e], sb + OFF_A + (kk < 2 ? s : sn) * 16384 + a_off + (((2 * ((kk + 2) & 3) + a_hx) ^ a_rx) << 4));
            pr[e] = lds128(tab + (kb * 4 + kk + 2) * 64);
          }
          WG_WAIT(1);
          if (kk == 0 && kb > 0 && lane == 0) {
            mbar_arrive(BAR(B_AE + ((n - 1) & 3)));
            mbar_arrive(BAR(B_BE + (kb + 4) % 5));
          }
        }
      }
      WG_WAIT(0);
      CSTAMP(11);
      if (lane == 0) {
        mbar_arrive(BAR(B_BE + 4));
        asm volatile("{\n.reg .b32 r;\nmapa.shared::cluster.u32 r, %0, %1;\nmbarrier.arrive.relaxed.cluster.shared::cluster.b64 _, [r];\n}"
                     ::"r"(BAR(B_PEER)), "r"(rank ^ 1u) : "memory");
      }
#pragma unroll
      for (int s = 0; s < 14; s++) {
        const float* src = s < 12 ? &accM[8 * s] : &accR[8 * (s - 12)];
#pragma unroll
        for (int e = 0; e < 4; e++) {
          const uint32_t v = pack2(gelu_half(src[2 * e]), gelu_half(src[2 * e + 1]));
          hfr[s][e] = (s >= 12 && bj >= 6) ? 0u : v;
          asm volatile("" : "+r"(hfr[s][e]));
        }
      }
    }
    CSTAMP(12);
    {
      G2Ctx c;
      c.sb = sb;
      asm volatile("mapa.shared::cluster.u32 %0, %1, %2;" : "=r"(c.peer) : "r"(sb), "r"(rank ^ 1u));
      c.par = ep1 & 1u; c.wg = wg; c.tw = tid & 127; c.lane = lane;
      c.srow = wr * 16 + (lane & 7) + ((lane >> 3) & 1) * 8;
      const int orow = bi * 128 + (bj >> 1) * 32 + (tid >> 3), ocol = (bj & 1) * 64 + (tid & 7) * 8;
      int nred = 0;
      float acc2[64];
      uint32_t pw_[32];
      uint4 rv[4], rx, rb;
      bool red = false;
      mbar_wait(BAR(B_PEER), 0);
      bar_sync(NB_CONS, 256);
      if (wg == 1) bar_sync(NB_SKEW, 256);
#pragma unroll 1
      for (int s = 0; s < 5; s++) {
        const int na = 10 + 2 * s, nb = na + 1;
        const uint32_t sa = dlo(sb + slot_b(na % 5), 14336), sbb = dlo(sb + slot_b(nb % 5), 10240);
        mbar_wait2(BAR(B_BF + na % 5), (na / 5) & 1, BAR(B_BF + nb % 5), (nb / 5) & 1);
        WG_FENCE();
        g2_steps<0, 7>(acc2, hfr, sa, sbb);
        WG_COMMIT();
        g2_steps<7, 14>(acc2, hfr, sa, sbb);
        WG_COMMIT();
        WG_WAIT(1);
        if (s == 0 && wg == 0) bar_arrive(NB_SKEW, 256);
        if (lane == 0) mbar_arrive(BAR(B_BE + na % 5));
        if (s >= 2) mbar_wait2(BAR(B_RX + 2 * s - 4 + wg), 0, BAR(s >= 3 ? B_SE + 2 * s - 6 + wg : B_PEER), 0);
        if (s > 0) g2_emit(pw_, c, s - 1);
        if (red && reduce_valid(rv, ep1)) { reduce_finish(p, sb, orow, ocol + nred * 128, rv, rx, rb); nred++; }
        red = s >= 3 && __all_sync(~0u, mbar_test(BAR(B_RF + nred), 0));
        if (red) reduce_load(p, orow, ocol + nred * 128, rv, rx, rb);
        WG_WAIT(0);
        if (tid == 0) PSTAMP(114 + 2 * s);
        if (lane == 0) mbar_arrive(BAR(B_BE + nb % 5));
#pragma unroll
        for (int e = 0; e < 32; e++) {
          pw_[e] = pack2(acc2[2 * e], acc2[2 * e + 1]);
          asm volatile("" : "+r"(pw_[e]));
        }
        if (tid == 0) PSTAMP(115 + 2 * s);
      }
      mbar_wait2(BAR(B_RX + 6 + wg), 0, BAR(B_RX + 8 + wg), 0);
      mbar_wait(BAR(B_SE + 4 + wg), 0);
      g2_emit(pw_, c, 4);
      if (red && reduce_valid(rv, ep1)) { reduce_finish(p, sb, orow, ocol + nred * 128, rv, rx, rb); nred++; }
      CSTAMP(13);
#pragma unroll 1
      for (int it = 0; nred < 5 && it < SPIN_LIMIT; it++) {
        uint4 v[4], xv, bv, v2[4], x2, b2;
        const int n2 = nred < 4 ? nred + 1 : nred;
        mbar_wait(BAR(B_RF + nred), 0);
        const bool two = nred < 4 && __all_sync(~0u, mbar_test(BAR(B_RF + n2), 0));
        reduce_load(p, orow, ocol + nred * 128, v, xv, bv);
        if (two) reduce_load(p, orow, ocol + n2 * 128, v2, x2, b2);
        if (reduce_valid(v, ep1)) {
          reduce_finish(p, sb, orow, ocol + nred * 128, v, xv, bv);
          nred++;
          if (two && reduce_valid(v2, ep1)) { reduce_finish(p, sb, orow, ocol + n2 * 128, v2, x2, b2); nred++; }
        }
      }
      CSTAMP(14);
      CSTAMP(15);
      if (tid == 0) GSTAMP(127);
    }
  }
}

typedef CUresult (*EncodeFn)(CUtensorMap*, CUtensorMapDataType, cuuint32_t, void*, const cuuint64_t*, const cuuint64_t*,
                             const cuuint32_t*, const cuuint32_t*, CUtensorMapInterleave, CUtensorMapSwizzle,
                             CUtensorMapL2promotion, CUtensorMapFloatOOBfill);

void encode(EncodeFn fn, CUtensorMap* m, const void* base, int rank, const cuuint64_t* dims, const cuuint64_t* strides,
            const cuuint32_t* box, CUtensorMapSwizzle sw) {
  const cuuint32_t es[4] = {1, 1, 1, 1};
  fn(m, CU_TENSOR_MAP_DATA_TYPE_BFLOAT16, rank, const_cast<void*>(base), dims, strides, box, es, CU_TENSOR_MAP_INTERLEAVE_NONE, sw,
     CU_TENSOR_MAP_L2_PROMOTION_L2_128B, CU_TENSOR_MAP_FLOAT_OOB_FILL_NONE);
}

int active_clusters(int cs) {
  cudaLaunchConfig_t cfg = {};
  cfg.gridDim = dim3(cs * 16);
  cfg.blockDim = dim3(384);
  cfg.dynamicSmemBytes = SMEM_BYTES;
  cudaLaunchAttribute a[1];
  a[0].id = cudaLaunchAttributeClusterDimension;
  a[0].val.clusterDim.x = cs; a[0].val.clusterDim.y = 1; a[0].val.clusterDim.z = 1;
  cfg.attrs = a; cfg.numAttrs = 1;
  int n = 0;
  if (cudaOccupancyMaxActiveClusters(&n, fused_block_kernel, &cfg) != cudaSuccess) { (void)cudaGetLastError(); return -1; }
  return n;
}

}

extern "C" void kernel_launch(void* const* d_in, const int* in_sizes, int n_in, void* d_out, int out_size) {
  (void)in_sizes; (void)n_in; (void)out_size;
  static bool ready = false;
  static TMaps tm;
  static Params p;
  static const void* key[11];
  bool same = ready && key[10] == d_out;
  for (int i = 0; i < 10 && same; i++) same = key[i] == d_in[i];
  if (!same) {
    for (int i = 0; i < 10; i++) key[i] = d_in[i];
    key[10] = d_out;
    void* fp = nullptr;
    cudaDriverEntryPointQueryResult qr;
    cudaGetDriverEntryPoint("cuTensorMapEncodeTiled", &fp, cudaEnableDefault, &qr);
    EncodeFn fn = (EncodeFn)fp;
    void *o_ptr, *x1_ptr, *part_ptr;
    cudaGetSymbolAddress(&o_ptr, g_o);
    cudaGetSymbolAddress(&x1_ptr, g_x1);
    cudaGetSymbolAddress(&part_ptr, g_part);
    const void *x = d_in[0], *wqkv = d_in[1], *wo = d_in[2], *w1 = d_in[4], *w2 = d_in[6];
    {
      const cuuint64_t d[2] = {640, 2048}, s[1] = {1280};
      const cuuint32_t b[2] = {64, 128};
      encode(fn, &tm.x, x, 2, d, s, b, CU_TENSOR_MAP_SWIZZLE_128B);
      encode(fn, &tm.o, o_ptr, 2, d, s, b, CU_TENSOR_MAP_SWIZZLE_128B);
      encode(fn, &tm.x1, x1_ptr, 2, d, s, b, CU_TENSOR_MAP_SWIZZLE_128B);
    }
    {
      const cuuint64_t d[3] = {640, 640, 3}, s[2] = {3840, 1280};
      const cuuint32_t bm[3] = {64, 64, 3}, br[3] = {16, 64, 3};
      encode(fn, &tm.wqkv_m, wqkv, 3, d, s, bm, CU_TENSOR_MAP_SWIZZLE_128B);
      encode(fn, &tm.wqkv_r, wqkv, 3, d, s, br, CU_TENSOR_MAP_SWIZZLE_32B);
    }
    {
      const cuuint64_t d[3] = {16, 640, 40}, s[2] = {1280, 32};
      const cuuint32_t b[3] = {16, 64, 5};
      encode(fn, &tm.wo, wo, 3, d, s, b, CU_TENSOR_MAP_SWIZZLE_32B);
    }
    {
      const cuuint64_t d[3] = {64, 640, 27}, s[2] = {3456, 128};
      const cuuint32_t b[3] = {64, 64, 3};
      encode(fn, &tm.w1_m, w1, 3, d, s, b, CU_TENSOR_MAP_SWIZZLE_128B);
      const cuuint64_t d2[2] = {1728, 640}, s2[1] = {3456};
      const cuuint32_t b2[2] = {32, 64};
      encode(fn, &tm.w1_r, w1, 2, d2, s2, b2, CU_TENSOR_MAP_SWIZZLE_64B);
    }
    {
      const cuuint64_t d[2] = {640, 1728}, s[1] = {1280};
      const cuuint32_t ba[2] = {64, 112}, bb[2] = {64, 80}, br[2] = {64, 32};
      encode(fn, &tm.w2_a, w2, 2, d, s, ba, CU_TENSOR_MAP_SWIZZLE_128B);
      encode(fn, &tm.w2_b, w2, 2, d, s, bb, CU_TENSOR_MAP_SWIZZLE_128B);
      encode(fn, &tm.w2_r, w2, 2, d, s, br, CU_TENSOR_MAP_SWIZZLE_128B);
    }
    {
      const cuuint64_t d[2] = {640, 4 * 2048}, s[1] = {1280};
      const cuuint32_t b[2] = {64, 64};
      encode(fn, &tm.part, part_ptr, 2, d, s, b, CU_TENSOR_MAP_SWIZZLE_128B);
    }
    {
      const cuuint64_t d[2] = {3840, 640}, s[1] = {7680};
      const cuuint32_t b[2] = {16, 160};
      encode(fn, &tm.wmod, d_in[9], 2, d, s, b, CU_TENSOR_MAP_SWIZZLE_NONE);
    }
    p.x = (const bf16*)x; p.wo = (const bf16*)wo; p.w1 = (const bf16*)w1; p.b1 = (const bf16*)d_in[5];
    p.w2 = (const bf16*)w2; p.b2 = (const bf16*)d_in[7]; p.c = (const bf16*)d_in[8];
    p.out = (bf16*)d_out;
    cudaFuncSetAttribute(fused_block_kernel, cudaFuncAttributeMaxDynamicSharedMemorySize, SMEM_BYTES);
    cudaFuncSetAttribute(fused_block_kernel, cudaFuncAttributeNonPortableClusterSizeAllowed, 1);
    int sms = 0;
    cudaDeviceGetAttribute(&sms, cudaDevAttrMultiProcessorCount, 0);
    p.use_smid = sms == NCTA && active_clusters(4) == 30 && active_clusters(8) == 15 && active_clusters(16) == 7;
    ready = true;
  }
  cudaLaunchConfig_t cfg = {};
  cfg.gridDim = dim3(NCTA);
  cfg.blockDim = dim3(384);
  cfg.dynamicSmemBytes = SMEM_BYTES;
  cfg.stream = cudaStreamPerThread;
  cudaLaunchAttribute at[1];
  at[0].id = cudaLaunchAttributeClusterDimension;
  at[0].val.clusterDim.x = 2; at[0].val.clusterDim.y = 1; at[0].val.clusterDim.z = 1;
  cfg.attrs = at; cfg.numAttrs = 1;
  cudaLaunchKernelEx(&cfg, fused_block_kernel, tm, p);
}
```

```cpp
#include <cuda_runtime.h>
#include <cuda_bf16.h>
#include <cuda.h>
#include <stdint.h>

#define DEVI __device__ __forceinline__
typedef __nv_bfloat16 bf16;

namespace {

constexpr int SEQ = 2048, DM = 640;
constexpr int HP = 1792;
constexpr int NCTA = 132;
constexpr int KV_ATOM = 2816;
constexpr int KV_HALF = 8 * KV_ATOM;
constexpr int KV_IMG = 2 * KV_HALF;
constexpr int SPIN_LIMIT = 1 << 17;

constexpr int OFF_A = 0;
constexpr int OFF_B = 65536;
constexpr int SLOT_B = 28672;
constexpr int SLOT_B1 = 30720;
constexpr int OFF_SLAB = 190464;
constexpr int OFF_C = OFF_SLAB + 20480;
constexpr int OFF_WO = 122880;
constexpr int OFF_T = 225280;
constexpr int OFF_TAB = OFF_T;
constexpr int OFF_GB = OFF_TAB + 2560;
constexpr int OFF_B1T = OFF_GB + 160;
constexpr int OFF_GA = OFF_B1T + 896;
constexpr int OFF_STB = OFF_GA + 320;
constexpr int OFF_CST = OFF_STB + 960;
constexpr int OFF_RED = OFF_CST + 64;
constexpr int OFF_B2 = OFF_RED + 384;
constexpr int OFF_BAR = OFF_B2 + 160;
constexpr int NBAR = 58;
constexpr int OFF_EP = OFF_BAR + NBAR * 8;
constexpr int SMEM_BYTES = OFF_EP + 16;
static_assert(SMEM_BYTES <= 232448, "smem");

constexpr int B_FULL1 = 0, B_SLAB = 4, B_SLABFREE = 5, B_EMPTY1 = 6, B_WOB = 10, B_AF = 12, B_AE = 16, B_BF = 20, B_BE = 25,
              B_QKVDONE = 30, B_TAB2 = 32, B_HS = 33  , B_X1G = 37, B_PEER = 38,
              B_KV = 39  , B_OPUB = 45, B_XPUB = 46, B_SLAB2 = 47, B_SLAB2FREE = 48, B_SPUB = 49,
              B_FIN = 50, B_OREL = 51, B_RX = 52  , B_HF = 55  ;
constexpr int NB_SETUP = 1, NB_CONS = 2, NB_GEMV = 5, NB_P23 = 6, NB_VOTE = 8;

struct alignas(64) TMaps {
  CUtensorMap x, wqkv_m, wqkv_r, wo, o, x1, w1_m, w1_r, wmod, h, h_r, w2_m, w2_n, w2_k, w2_kn, x1g;
};
struct Params {
  const bf16 *x, *wo, *w1, *b1, *w2, *b2, *c;
  bf16* out;
  int use_smid;
};

__device__ uint4 g_kv[128 * (KV_IMG / 16)];
__device__ uint4 g_o[SEQ * DM / 8];
__device__ uint4 g_x1[SEQ * DM / 8];
__device__ uint4 g_h[SEQ * HP / 8];
__device__ uint4 g_stats[SEQ * 8 * 2];
__device__ uint4 g_fin[SEQ];
__device__ unsigned long long g_mod[1920];
__device__ unsigned long long g_st1[SEQ];
__device__ unsigned int g_flag_kv[128 * 16];
__device__ unsigned int g_flag_o[16 * 32];
__device__ unsigned int g_flag_x1[16 * 32];
__device__ unsigned int g_flag_h[128 * 32];
__device__ unsigned long long g_ticket;

DEVI uint32_t slot_b(int s) { return OFF_B + (s < 2 ? s : 6 - s) * SLOT_B; }
DEVI uint32_t s2u(const void* p) { return (uint32_t)__cvta_generic_to_shared(p); }
DEVI void mbar_init(uint32_t b, uint32_t c) { asm volatile("mbarrier.init.shared::cta.b64 [%0], %1;" ::"r"(b), "r"(c) : "memory"); }
template <int I0, int I1>
DEVI void init_barriers(uint32_t bar) {
  constexpr unsigned long long M8 = (0xfull << B_EMPTY1) | (0xfull << B_AE) | (0x1full << B_BE) | (1ull << B_QKVDONE) |
                                    (1ull << B_OPUB) | (1ull << B_XPUB) | (1ull << B_PEER) | (1ull << B_SLABFREE) |
                                    (7ull << B_HS) | (1ull << B_SPUB);
#pragma unroll
  for (int i = I0; i < I1; i++)
    mbar_init(bar + 8 * i, (M8 >> i & 1) ? 8 : i == B_KV + 4 || i == B_KV + 5 ? 128 :
                           i == B_TAB2 ? 64 : i == B_SLAB2FREE ? 2 : 1);
  asm volatile("fence.mbarrier_init.release.cluster;" ::: "memory");
}
DEVI void mbar_expect(uint32_t b, uint32_t bytes) {
  asm volatile("mbarrier.arrive.expect_tx.shared::cta.b64 _, [%0], %1;" ::"r"(b), "r"(bytes) : "memory");
}
DEVI void mbar_arrive(uint32_t b) { asm volatile("mbarrier.arrive.shared::cta.b64 _, [%0];" ::"r"(b) : "memory"); }
DEVI void mbar_wait(uint32_t b, uint32_t parity) {
  asm volatile(
      "{\n.reg .pred p;\n.reg .u32 c;\nmov.u32 c, %2;\n"
      "W: mbarrier.try_wait.parity.shared::cta.b64 p, [%0], %1;\n@p bra D;\n"
      "sub.u32 c, c, 1;\nsetp.ne.u32 p, c, 0;\n@p bra W;\nD:\n}" ::"r"(b), "r"(parity), "n"(SPIN_LIMIT) : "memory");
}
DEVI void mbar_wait2(uint32_t b0, uint32_t p0, uint32_t b1, uint32_t p1) {
  asm volatile(
      "{\n.reg .pred p, q;\n.reg .u32 c;\nmov.u32 c, %4;\n"
      "W: mbarrier.try_wait.parity.shared::cta.b64 p, [%0], %1;\n"
      "mbarrier.try_wait.parity.shared::cta.b64 q, [%2], %3;\n"
      "and.pred p, p, q;\n@p bra D;\n"
      "sub.u32 c, c, 1;\nsetp.ne.u32 p, c, 0;\n@p bra W;\nD:\n}" ::"r"(b0), "r"(p0), "r"(b1), "r"(p1), "n"(SPIN_LIMIT) : "memory");
}
DEVI void bar_sync(int id, int n) { asm volatile("bar.sync %0, %1;" ::"r"(id), "r"(n) : "memory"); }
DEVI void bar_arrive(int id, int n) { asm volatile("bar.arrive %0, %1;" ::"r"(id), "r"(n) : "memory"); }
DEVI void poll_ge(const unsigned int* p, unsigned int target) {
  unsigned int v;
  int it = 0;
  do {
    asm volatile("ld.acquire.gpu.global.u32 %0, [%1];" : "=r"(v) : "l"(p) : "memory");
  } while ((int)(v - target) < 0 && ++it < SPIN_LIMIT);
}
DEVI void red_release(unsigned int* p) { asm volatile("red.release.gpu.global.add.u32 [%0], 1;" ::"l"(p) : "memory"); }
DEVI void ll_store16(uint4* p, float a, float b, float c, uint32_t tag) {
  asm volatile("{\n.reg .b128 v;\nmov.b128 v, {%1, %2};\nst.relaxed.gpu.global.b128 [%0], v;\n}" ::"l"(p),
               "l"(((unsigned long long)__float_as_uint(b) << 32) | __float_as_uint(a)),
               "l"(((unsigned long long)tag << 32) | __float_as_uint(c)) : "memory");
}
DEVI uint4 ll_load16(const uint4* p) {
  unsigned long long a, b;
  asm volatile("{\n.reg .b128 v;\nld.relaxed.gpu.global.b128 v, [%2];\nmov.b128 {%0, %1}, v;\n}" : "=l"(a), "=l"(b) : "l"(p) : "memory");
  return make_uint4((uint32_t)a, (uint32_t)(a >> 32), (uint32_t)b, (uint32_t)(b >> 32));
}
DEVI void ll_store(unsigned long long* p, uint32_t data, uint32_t tag) {
  asm volatile("st.relaxed.gpu.global.u64 [%0], %1;" ::"l"(p), "l"(((unsigned long long)tag << 32) | data) : "memory");
}
DEVI void fence_async_gmem() { asm volatile("fence.proxy.async.global;" ::: "memory"); }
DEVI void fence_async_smem() { asm volatile("fence.proxy.async.shared::cta;" ::: "memory"); }
DEVI void tma2(uint32_t dst, const CUtensorMap* m, uint32_t bar, int c0, int c1) {
  asm volatile("cp.async.bulk.tensor.2d.shared::cluster.global.mbarrier::complete_tx::bytes [%0], [%1, {%3, %4}], [%2];"
               ::"r"(dst), "l"(m), "r"(bar), "r"(c0), "r"(c1) : "memory");
}
DEVI void tma3(uint32_t dst, const CUtensorMap* m, uint32_t bar, int c0, int c1, int c2) {
  asm volatile("cp.async.bulk.tensor.3d.shared::cluster.global.mbarrier::complete_tx::bytes [%0], [%1, {%3, %4, %5}], [%2];"
               ::"r"(dst), "l"(m), "r"(bar), "r"(c0), "r"(c1), "r"(c2) : "memory");
}
DEVI void tma2_store(const CUtensorMap* m, uint32_t src, int c0, int c1) {
  asm volatile("cp.async.bulk.tensor.2d.global.shared::cta.bulk_group [%0, {%2, %3}], [%1];" ::"l"(m), "r"(src), "r"(c0), "r"(c1) : "memory");
}
DEVI void bulk_load(uint32_t dst, const void* src, uint32_t bytes, uint32_t bar) {
  asm volatile("cp.async.bulk.shared::cluster.global.mbarrier::complete_tx::bytes [%0], [%1], %2, [%3];"
               ::"r"(dst), "l"(src), "r"(bytes), "r"(bar) : "memory");
}
DEVI void bulk_store(void* dst, uint32_t src, uint32_t bytes) {
  asm volatile("cp.async.bulk.global.shared::cta.bulk_group [%0], [%1], %2;" ::"l"(dst), "r"(src), "r"(bytes) : "memory");
}
DEVI void bulk_commit() { asm volatile("cp.async.bulk.commit_group;" ::: "memory"); }
DEVI void bulk_wait1() { asm volatile("cp.async.bulk.wait_group 1;" ::: "memory"); }
DEVI void bulk_wait0() { asm volatile("cp.async.bulk.wait_group 0;" ::: "memory"); }
DEVI void l2_prefetch(const void* p, uint32_t bytes) {
  asm volatile("cp.async.bulk.prefetch.L2.global [%0], %1;" ::"l"(p), "r"(bytes) : "memory");
}
DEVI uint32_t dlo(uint32_t addr, uint32_t lbo) { return ((addr & 0x3FFFF) >> 4) | ((lbo >> 4) << 16); }
DEVI uint64_t mkdesc(uint32_t lo, uint32_t off, uint32_t sbo, uint32_t sw) {
  return (uint64_t)(lo + (off >> 4)) | ((uint64_t)((sbo >> 4) | (sw << 30)) << 32);
}
#define WG_FENCE() asm volatile("wgmma.fence.sync.aligned;" ::: "memory")
#define WG_COMMIT() asm volatile("wgmma.commit_group.sync.aligned;" ::: "memory")
#define WG_WAIT(n) asm volatile("wgmma.wait_group.sync.aligned %0;" ::"n"(n) : "memory")
DEVI void ldsm4(uint32_t (&r)[4], uint32_t addr) {
  asm volatile("ldmatrix.sync.aligned.m8n8.x4.shared.b16 {%0,%1,%2,%3}, [%4];"
               : "=r"(r[0]), "=r"(r[1]), "=r"(r[2]), "=r"(r[3]) : "r"(addr) : "memory");
}
DEVI void ldsm4t(uint32_t (&r)[4], uint32_t addr) {
  asm volatile("ldmatrix.sync.aligned.m8n8.x4.trans.shared.b16 {%0,%1,%2,%3}, [%4];"
               : "=r"(r[0]), "=r"(r[1]), "=r"(r[2]), "=r"(r[3]) : "r"(addr) : "memory");
}
DEVI void mma_rows8(float (&d)[4], uint32_t a0, uint32_t a2, uint32_t b0, uint32_t b1) {
  asm volatile("mma.sync.aligned.m16n8k16.row.col.f32.bf16.bf16.f32 {%0,%1,%2,%3}, {%4,%5,%6,%5}, {%7,%8}, {%0,%1,%2,%3};"
               : "+f"(d[0]), "+f"(d[1]), "+f"(d[2]), "+f"(d[3]) : "r"(a0), "r"(0u), "r"(a2), "r"(b0), "r"(b1));
}
DEVI void mma16816(float (&d)[4], const uint32_t (&a)[4], uint32_t b0, uint32_t b1) {
  asm volatile("mma.sync.aligned.m16n8k16.row.col.f32.bf16.bf16.f32 {%0,%1,%2,%3}, {%4,%5,%6,%7}, {%8,%9}, {%0,%1,%2,%3};"
               : "+f"(d[0]), "+f"(d[1]), "+f"(d[2]), "+f"(d[3]) : "r"(a[0]), "r"(a[1]), "r"(a[2]), "r"(a[3]), "r"(b0), "r"(b1));
}
DEVI uint32_t hmul2(uint32_t a, uint32_t b) {
  uint32_t r;
  asm("mul.rn.bf16x2 %0, %1, %2;" : "=r"(r) : "r"(a), "r"(b));
  return r;
}
DEVI void stsm4(uint32_t addr, uint32_t a, uint32_t b, uint32_t c, uint32_t d) {
  asm volatile("stmatrix.sync.aligned.m8n8.x4.shared.b16 [%0], {%1,%2,%3,%4};" ::"r"(addr), "r"(a), "r"(b), "r"(c), "r"(d) : "memory");
}
DEVI uint4 lds128(uint32_t a) {
  uint4 v;
  asm volatile("ld.shared.v4.u32 {%0,%1,%2,%3}, [%4];" : "=r"(v.x), "=r"(v.y), "=r"(v.z), "=r"(v.w) : "r"(a) : "memory");
  return v;
}
DEVI uint2 lds64(uint32_t a) {
  uint2 v;
  asm volatile("ld.shared.v2.u32 {%0,%1}, [%2];" : "=r"(v.x), "=r"(v.y) : "r"(a) : "memory");
  return v;
}
DEVI uint32_t lds32(uint32_t a) {
  uint32_t v;
  asm volatile("ld.shared.u32 %0, [%1];" : "=r"(v) : "r"(a) : "memory");
  return v;
}
DEVI void sts32(uint32_t a, uint32_t v) { asm volatile("st.shared.u32 [%0], %1;" ::"r"(a), "r"(v) : "memory"); }
DEVI void sts64(uint32_t a, uint32_t x, uint32_t y) { asm volatile("st.shared.v2.u32 [%0], {%1,%2};" ::"r"(a), "r"(x), "r"(y) : "memory"); }
DEVI void sts128(uint32_t a, uint4 v) {
  asm volatile("st.shared.v4.u32 [%0], {%1,%2,%3,%4};" ::"r"(a), "r"(v.x), "r"(v.y), "r"(v.z), "r"(v.w) : "memory");
}
DEVI uint4 ldg_nc(const void* p) {
  uint4 v;
  asm volatile("ld.global.nc.L1::no_allocate.v4.u32 {%0,%1,%2,%3}, [%4];" : "=r"(v.x), "=r"(v.y), "=r"(v.z), "=r"(v.w) : "l"(p));
  return v;
}
DEVI uint4 ldg_cg(const void* p) {
  uint4 v;
  asm volatile("ld.global.cg.v4.u32 {%0,%1,%2,%3}, [%4];" : "=r"(v.x), "=r"(v.y), "=r"(v.z), "=r"(v.w) : "l"(p) : "memory");
  return v;
}
DEVI void stg128(void* p, uint4 v) {
  asm volatile("st.global.v4.u32 [%0], {%1,%2,%3,%4};" ::"l"(p), "r"(v.x), "r"(v.y), "r"(v.z), "r"(v.w) : "memory");
}
DEVI uint32_t pack2(float lo, float hi) {
  uint32_t r;
  asm("cvt.rn.bf16x2.f32 %0, %1, %2;" : "=r"(r) : "f"(hi), "f"(lo));
  return r;
}
DEVI float bf_lo(uint32_t v) { return __uint_as_float(v << 16); }
DEVI float bf_hi(uint32_t v) { return __uint_as_float(v & 0xffff0000u); }
DEVI uint32_t hfma2(uint32_t a, uint32_t b, uint32_t c) {
  uint32_t r;
  asm("fma.rn.bf16x2 %0, %1, %2, %3;" : "=r"(r) : "r"(a), "r"(b), "r"(c));
  return r;
}
DEVI float ex2(float x) {
  float r;
  asm("ex2.approx.ftz.f32 %0, %1;" : "=f"(r) : "f"(x));
  return r;
}
DEVI float ex2v(float x) {
  float r;
  asm volatile("ex2.approx.ftz.f32 %0, %1;" : "=f"(r) : "f"(x));
  return r;
}
DEVI uint32_t gelu_half2(float z0, float z1) {
  const uint32_t z = pack2(z0, z1);
  uint32_t z2, u, t;
  asm("mul.rn.bf16x2 %0, %1, %1;" : "=r"(z2) : "r"(z));
  const uint32_t pl = hfma2(z2, 0x3e923e92u, 0x3fcc3fccu);
  asm("mul.rn.bf16x2 %0, %1, %2;" : "=r"(u) : "r"(z), "r"(pl));
  asm("tanh.approx.bf16x2 %0, %1;" : "=r"(t) : "r"(u));
  return hfma2(z, t, z);
}
DEVI float silu_f(float x) { return __fdividef(x, 1.0f + ex2(-1.4426950408889634f * x)); }

__device__ __forceinline__ void wgmma_rs_n192_t1(float (&d)[96], const uint32_t (&a)[4], uint64_t db, int sd) {
  asm volatile("{\n.reg .pred p;\nsetp.ne.b32 p, %101, 0;\nwgmma.mma_async.sync.aligned.m64n192k16.f32.bf16.bf16 "
    "{%0, %1, %2, %3, %4, %5, %6, %7, %8, %9, %10, %11, %12, %13, %14, %15, %16, %17, %18, %19, %20, %21, %22, %23, %24, %25, %26, %27, %28, %29, %30, %31, %32, %33, %34, %35, %36, %37, %38, %39, %40, %41, %42, %43, %44, %45, %46, %47, %48, %49, %50, %51, %52, %53, %54, %55, %56, %57, %58, %59, %60, %61, %62, %63, %64, %65, %66, %67, %68, %69, %70, %71, %72, %73, %74, %75, %76, %77, %78, %79, %80, %81, %82, %83, %84, %85, %86, %87, %88, %89, %90, %91, %92, %93, %94, %95}, {%96, %97, %98, %99}, %100, p, 1, 1, 1;\n}\n"
    : "+f"(d[0]), "+f"(d[1]), "+f"(d[2]), "+f"(d[3]), "+f"(d[4]), "+f"(d[5]), "+f"(d[6]), "+f"(d[7]), "+f"(d[8]), "+f"(d[9]), "+f"(d[10]), "+f"(d[11]), "+f"(d[12]), "+f"(d[13]), "+f"(d[14]), "+f"(d[15]), "+f"(d[16]), "+f"(d[17]), "+f"(d[18]), "+f"(d[19]), "+f"(d[20]), "+f"(d[21]), "+f"(d[22]), "+f"(d[23]), "+f"(d[24]), "+f"(d[25]), "+f"(d[26]), "+f"(d[27]), "+f"(d[28]), "+f"(d[29]), "+f"(d[30]), "+f"(d[31]), "+f"(d[32]), "+f"(d[33]), "+f"(d[34]), "+f"(d[35]), "+f"(d[36]), "+f"(d[37]), "+f"(d[38]), "+f"(d[39]), "+f"(d[40]), "+f"(d[41]), "+f"(d[42]), "+f"(d[43]), "+f"(d[44]), "+f"(d[45]), "+f"(d[46]), "+f"(d[47]), "+f"(d[48]), "+f"(d[49]), "+f"(d[50]), "+f"(d[51]), "+f"(d[52]), "+f"(d[53]), "+f"(d[54]), "+f"(d[55]), "+f"(d[56]), "+f"(d[57]), "+f"(d[58]), "+f"(d[59]), "+f"(d[60]), "+f"(d[61]), "+f"(d[62]), "+f"(d[63]), "+f"(d[64]), "+f"(d[65]), "+f"(d[66]), "+f"(d[67]), "+f"(d[68]), "+f"(d[69]), "+f"(d[70]), "+f"(d[71]), "+f"(d[72]), "+f"(d[73]), "+f"(d[74]), "+f"(d[75]), "+f"(d[76]), "+f"(d[77]), "+f"(d[78]), "+f"(d[79]), "+f"(d[80]), "+f"(d[81]), "+f"(d[82]), "+f"(d[83]), "+f"(d[84]), "+f"(d[85]), "+f"(d[86]), "+f"(d[87]), "+f"(d[88]), "+f"(d[89]), "+f"(d[90]), "+f"(d[91]), "+f"(d[92]), "+f"(d[93]), "+f"(d[94]), "+f"(d[95])
    : "r"(a[0]), "r"(a[1]), "r"(a[2]), "r"(a[3]), "l"(db), "r"(sd));
}
__device__ __forceinline__ void wgmma_rs_n48_t1(float (&d)[24], const uint32_t (&a)[4], uint64_t db, int sd) {
  asm volatile("{\n.reg .pred p;\nsetp.ne.b32 p, %29, 0;\nwgmma.mma_async.sync.aligned.m64n48k16.f32.bf16.bf16 "
    "{%0, %1, %2, %3, %4, %5, %6, %7, %8, %9, %10, %11, %12, %13, %14, %15, %16, %17, %18, %19, %20, %21, %22, %23}, {%24, %25, %26, %27}, %28, p, 1, 1, 1;\n}\n"
    : "+f"(d[0]), "+f"(d[1]), "+f"(d[2]), "+f"(d[3]), "+f"(d[4]), "+f"(d[5]), "+f"(d[6]), "+f"(d[7]), "+f"(d[8]), "+f"(d[9]), "+f"(d[10]), "+f"(d[11]), "+f"(d[12]), "+f"(d[13]), "+f"(d[14]), "+f"(d[15]), "+f"(d[16]), "+f"(d[17]), "+f"(d[18]), "+f"(d[19]), "+f"(d[20]), "+f"(d[21]), "+f"(d[22]), "+f"(d[23])
    : "r"(a[0]), "r"(a[1]), "r"(a[2]), "r"(a[3]), "l"(db), "r"(sd));
}
__device__ __forceinline__ void wgmma_rs_n64_t0(float (&d)[32], const uint32_t (&a)[4], uint64_t db, int sd) {
  asm volatile("{\n.reg .pred p;\nsetp.ne.b32 p, %37, 0;\nwgmma.mma_async.sync.aligned.m64n64k16.f32.bf16.bf16 "
    "{%0, %1, %2, %3, %4, %5, %6, %7, %8, %9, %10, %11, %12, %13, %14, %15, %16, %17, %18, %19, %20, %21, %22, %23, %24, %25, %26, %27, %28, %29, %30, %31}, {%32, %33, %34, %35}, %36, p, 1, 1, 0;\n}\n"
    : "+f"(d[0]), "+f"(d[1]), "+f"(d[2]), "+f"(d[3]), "+f"(d[4]), "+f"(d[5]), "+f"(d[6]), "+f"(d[7]), "+f"(d[8]), "+f"(d[9]), "+f"(d[10]), "+f"(d[11]), "+f"(d[12]), "+f"(d[13]), "+f"(d[14]), "+f"(d[15]), "+f"(d[16]), "+f"(d[17]), "+f"(d[18]), "+f"(d[19]), "+f"(d[20]), "+f"(d[21]), "+f"(d[22]), "+f"(d[23]), "+f"(d[24]), "+f"(d[25]), "+f"(d[26]), "+f"(d[27]), "+f"(d[28]), "+f"(d[29]), "+f"(d[30]), "+f"(d[31])
    : "r"(a[0]), "r"(a[1]), "r"(a[2]), "r"(a[3]), "l"(db), "r"(sd));
}
__device__ __forceinline__ void wgmma_rs_n24_t1(float (&d)[12], const uint32_t (&a)[4], uint64_t db, int sd) {
  asm volatile("{\n.reg .pred p;\nsetp.ne.b32 p, %17, 0;\nwgmma.mma_async.sync.aligned.m64n24k16.f32.bf16.bf16 "
    "{%0, %1, %2, %3, %4, %5, %6, %7, %8, %9, %10, %11}, {%12, %13, %14, %15}, %16, p, 1, 1, 1;\n}\n"
    : "+f"(d[0]), "+f"(d[1]), "+f"(d[2]), "+f"(d[3]), "+f"(d[4]), "+f"(d[5]), "+f"(d[6]), "+f"(d[7]), "+f"(d[8]), "+f"(d[9]), "+f"(d[10]), "+f"(d[11])
    : "r"(a[0]), "r"(a[1]), "r"(a[2]), "r"(a[3]), "l"(db), "r"(sd));
}
__device__ __forceinline__ void wgmma_ss_n80_t1(float (&d)[40], uint64_t da, uint64_t db, int sd) {
  asm volatile("{\n.reg .pred p;\nsetp.ne.b32 p, %42, 0;\nwgmma.mma_async.sync.aligned.m64n80k16.f32.bf16.bf16 "
    "{%0, %1, %2, %3, %4, %5, %6, %7, %8, %9, %10, %11, %12, %13, %14, %15, %16, %17, %18, %19, %20, %21, %22, %23, %24, %25, %26, %27, %28, %29, %30, %31, %32, %33, %34, %35, %36, %37, %38, %39}, %40, %41, p, 1, 1, 0, 1;\n}\n"
    : "+f"(d[0]), "+f"(d[1]), "+f"(d[2]), "+f"(d[3]), "+f"(d[4]), "+f"(d[5]), "+f"(d[6]), "+f"(d[7]), "+f"(d[8]), "+f"(d[9]), "+f"(d[10]), "+f"(d[11]), "+f"(d[12]), "+f"(d[13]), "+f"(d[14]), "+f"(d[15]), "+f"(d[16]), "+f"(d[17]), "+f"(d[18]), "+f"(d[19]), "+f"(d[20]), "+f"(d[21]), "+f"(d[22]), "+f"(d[23]), "+f"(d[24]), "+f"(d[25]), "+f"(d[26]), "+f"(d[27]), "+f"(d[28]), "+f"(d[29]), "+f"(d[30]), "+f"(d[31]), "+f"(d[32]), "+f"(d[33]), "+f"(d[34]), "+f"(d[35]), "+f"(d[36]), "+f"(d[37]), "+f"(d[38]), "+f"(d[39])
    : "l"(da), "l"(db), "r"(sd));
}
__device__ __forceinline__ void wgmma_rs_n32_t1(float (&d)[16], const uint32_t (&a)[4], uint64_t db, int sd) {
  asm volatile("{\n.reg .pred p;\nsetp.ne.b32 p, %21, 0;\nwgmma.mma_async.sync.aligned.m64n32k16.f32.bf16.bf16 "
    "{%0, %1, %2, %3, %4, %5, %6, %7, %8, %9, %10, %11, %12, %13, %14, %15}, {%16, %17, %18, %19}, %20, p, 1, 1, 1;\n}\n"
    : "+f"(d[0]), "+f"(d[1]), "+f"(d[2]), "+f"(d[3]), "+f"(d[4]), "+f"(d[5]), "+f"(d[6]), "+f"(d[7]), "+f"(d[8]), "+f"(d[9]), "+f"(d[10]), "+f"(d[11]), "+f"(d[12]), "+f"(d[13]), "+f"(d[14]), "+f"(d[15])
    : "r"(a[0]), "r"(a[1]), "r"(a[2]), "r"(a[3]), "l"(db), "r"(sd));
}
__device__ __forceinline__ void wgmma_rs_n128_t1(float (&d)[64], const uint32_t (&a)[4], uint64_t db, int sd) {
  asm volatile("{\n.reg .pred p;\nsetp.ne.b32 p, %69, 0;\nwgmma.mma_async.sync.aligned.m64n128k16.f32.bf16.bf16 "
    "{%0, %1, %2, %3, %4, %5, %6, %7, %8, %9, %10, %11, %12, %13, %14, %15, %16, %17, %18, %19, %20, %21, %22, %23, %24, %25, %26, %27, %28, %29, %30, %31, %32, %33, %34, %35, %36, %37, %38, %39, %40, %41, %42, %43, %44, %45, %46, %47, %48, %49, %50, %51, %52, %53, %54, %55, %56, %57, %58, %59, %60, %61, %62, %63}, {%64, %65, %66, %67}, %68, p, 1, 1, 1;\n}\n"
    : "+f"(d[0]), "+f"(d[1]), "+f"(d[2]), "+f"(d[3]), "+f"(d[4]), "+f"(d[5]), "+f"(d[6]), "+f"(d[7]), "+f"(d[8]), "+f"(d[9]), "+f"(d[10]), "+f"(d[11]), "+f"(d[12]), "+f"(d[13]), "+f"(d[14]), "+f"(d[15]), "+f"(d[16]), "+f"(d[17]), "+f"(d[18]), "+f"(d[19]), "+f"(d[20]), "+f"(d[21]), "+f"(d[22]), "+f"(d[23]), "+f"(d[24]), "+f"(d[25]), "+f"(d[26]), "+f"(d[27]), "+f"(d[28]), "+f"(d[29]), "+f"(d[30]), "+f"(d[31]), "+f"(d[32]), "+f"(d[33]), "+f"(d[34]), "+f"(d[35]), "+f"(d[36]), "+f"(d[37]), "+f"(d[38]), "+f"(d[39]), "+f"(d[40]), "+f"(d[41]), "+f"(d[42]), "+f"(d[43]), "+f"(d[44]), "+f"(d[45]), "+f"(d[46]), "+f"(d[47]), "+f"(d[48]), "+f"(d[49]), "+f"(d[50]), "+f"(d[51]), "+f"(d[52]), "+f"(d[53]), "+f"(d[54]), "+f"(d[55]), "+f"(d[56]), "+f"(d[57]), "+f"(d[58]), "+f"(d[59]), "+f"(d[60]), "+f"(d[61]), "+f"(d[62]), "+f"(d[63])
    : "r"(a[0]), "r"(a[1]), "r"(a[2]), "r"(a[3]), "l"(db), "r"(sd));
}
__device__ __forceinline__ void wgmma_rz_n64_t0(float (&d)[32], const uint32_t (&a)[4], uint64_t db) {
  asm volatile("wgmma.mma_async.sync.aligned.m64n64k16.f32.bf16.bf16 "
    "{%0, %1, %2, %3, %4, %5, %6, %7, %8, %9, %10, %11, %12, %13, %14, %15, %16, %17, %18, %19, %20, %21, %22, %23, %24, %25, %26, %27, %28, %29, %30, %31}, {%32, %33, %34, %35}, %36, 0, 1, 1, 0;\n"
    : "=f"(d[0]), "=f"(d[1]), "=f"(d[2]), "=f"(d[3]), "=f"(d[4]), "=f"(d[5]), "=f"(d[6]), "=f"(d[7]), "=f"(d[8]), "=f"(d[9]), "=f"(d[10]), "=f"(d[11]), "=f"(d[12]), "=f"(d[13]), "=f"(d[14]), "=f"(d[15]), "=f"(d[16]), "=f"(d[17]), "=f"(d[18]), "=f"(d[19]), "=f"(d[20]), "=f"(d[21]), "=f"(d[22]), "=f"(d[23]), "=f"(d[24]), "=f"(d[25]), "=f"(d[26]), "=f"(d[27]), "=f"(d[28]), "=f"(d[29]), "=f"(d[30]), "=f"(d[31])
    : "r"(a[0]), "r"(a[1]), "r"(a[2]), "r"(a[3]), "l"(db));
}


DEVI void gemv_part(uint32_t sb, int row0, int steps, int lane, uint32_t red_w) {
  float d0[4] = {0.f, 0.f, 0.f, 0.f}, d1[4] = {0.f, 0.f, 0.f, 0.f};
  const uint32_t m = lane < 4 ? ~0u : 0u;
#pragma unroll 5
  for (int k = 0; k < steps; k++) {
    uint32_t b[4];
    ldsm4t(b, sb + OFF_SLAB + (row0 + 16 * k + (lane & 15)) * 32 + (lane >> 4) * 16);
    const uint32_t ca = sb + OFF_C + (row0 + 16 * k) * 2 + (lane & 3) * 4, a0 = lds32(ca) & m, a2 = lds32(ca + 16) & m;
    mma_rows8(d0, a0, a2, b[0], b[1]);
    mma_rows8(d1, a0, a2, b[2], b[3]);
  }
  if (lane < 4) {
    sts64(red_w + lane * 8, __float_as_uint(d0[0]), __float_as_uint(d0[1]));
    sts64(red_w + 32 + lane * 8, __float_as_uint(d1[0]), __float_as_uint(d1[1]));
  }
  __syncwarp();
}
template <int NW>
DEVI void gemv_final(uint32_t red, int grp, int lane, uint32_t tag) {
  if (lane < 8) {
    float s0 = 0.f, s1 = 0.f;
#pragma unroll
    for (int w = 0; w < NW; w++) {
      uint2 v = lds64(red + w * 64 + lane * 8);
      s0 += __uint_as_float(v.x);
      s1 += __uint_as_float(v.y);
    }
    ll_store(&g_mod[grp * 8 + lane], pack2(s0, s1), tag);
  }
}

DEVI void stage_to_global(uint32_t p0, uint32_t p1, bf16* dst, int lane) {
#pragma unroll
  for (int m = 0; m < 4; m++) {
    int row = m * 4 + (lane >> 3), ch = lane & 7;
    uint4 v = lds128(p0 + row * 128 + ((ch ^ (row & 7)) << 4));
    stg128(dst + row * DM + ch * 8, v);
  }
  int row = lane >> 1, ch = lane & 1;
  uint4 v = lds128(p1 + row * 32 + ch * 16);
  stg128(dst + row * DM + 64 + ch * 8, v);
}

template <int H>
DEVI void qk_issue(float (&S)[32], const uint32_t (&qm)[4][2][4], uint32_t kv) {
  WG_FENCE();
  wgmma_rz_n64_t0(S, qm[H][0], mkdesc(kv, H * 256, KV_ATOM, 3));
  wgmma_rs_n64_t0(S, qm[H][1], mkdesc(kv, (H + 1) * 256, KV_ATOM, 3), 1);
  WG_COMMIT();
}
template <int H>
DEVI void pv_issue(float (&O)[12], const uint32_t (&P)[4][4], uint32_t kv) {
  WG_FENCE();
#pragma unroll
  for (int u = 0; u < 4; u++) wgmma_rs_n24_t1(O, P[u], mkdesc(kv, 1280 + H * 384 + u * 2 * KV_ATOM, 128, 0), 1);
  WG_COMMIT();
}
DEVI void exp_group(const float* S, uint32_t (&P)[4], const uint32_t (&m)[3]) {
  P[0] = pack2(ex2v(S[0]), ex2v(S[1]));
  P[1] = pack2(ex2v(S[2]), ex2v(S[3]));
  P[2] = pack2(ex2v(S[4]), ex2v(S[5]));
  P[3] = pack2(ex2v(S[6]), ex2v(S[7]));
  P[0] &= m[0]; P[1] &= m[1]; P[2] &= m[2]; P[3] &= m[0];
}
template <int H, int U>
DEVI void pv_step(float (&O)[12], const uint32_t (&P)[4], uint32_t kv) {
  WG_FENCE();
  wgmma_rs_n24_t1(O, P, mkdesc(kv, 1280 + H * 384 + U * 2 * KV_ATOM, 128, 0), 1);
}
template <int H>
DEVI void att_head(float (&O)[4][12], const float (&S)[32], float (&Sn)[32], uint32_t (&P)[4][4], const uint32_t (&qm)[4][2][4],
                   uint32_t kv, const uint32_t (&m)[4][3]) {
  exp_group(&S[0], P[0], m[0]);
  if constexpr (H > 0) {
    pv_step<H - 1, 3>(O[H - 1], P[3], kv);
    WG_COMMIT();
  }
  if constexpr (H < 3) qk_issue<H + 1>(Sn, qm, kv);
  if constexpr (H > 0) WG_WAIT(H < 3 ? 2 : 1);
  exp_group(&S[8], P[1], m[1]);
  pv_step<H, 0>(O[H], P[0], kv);
  exp_group(&S[16], P[2], m[2]);
  pv_step<H, 1>(O[H], P[1], kv);
  WG_COMMIT();
  if constexpr (H > 0) WG_WAIT(H < 3 ? 2 : 1);
  exp_group(&S[24], P[3], m[3]);
  pv_step<H, 2>(O[H], P[2], kv);
  WG_COMMIT();
  if constexpr (H < 3) WG_WAIT(1);
}
DEVI void att_fast_piece(float (&O)[4][12], const uint32_t (&qm)[4][2][4], uint32_t kv, const uint32_t (&m)[4][3]) {
  float S0[32], S1[32];
  uint32_t P[4][4];
  qk_issue<0>(S0, qm, kv);
  WG_WAIT(0);
  att_head<0>(O, S0, S1, P, qm, kv, m);
  att_head<1>(O, S1, S0, P, qm, kv, m);
  att_head<2>(O, S0, S1, P, qm, kv, m);
  att_head<3>(O, S1, S0, P, qm, kv, m);
  pv_step<3, 3>(O[3], P[3], kv);
  WG_COMMIT();
  WG_WAIT(0);
}
DEVI void softmax_slab(float (&S)[32], uint32_t (&P)[4][4], float (&O)[12], float& m0, float& m1, int lo, int hi,
                       int pu, bool k0, bool k1, bool diag) {
  const float NEG = __int_as_float(0xff800000);
  float x0 = m0, x1 = m1;
#pragma unroll
  for (int u = 0; u < 4; u++) {
    if (u == pu) {
      S[8 * u + 0] = k0 ? S[8 * u + 0] : NEG;
      S[8 * u + 1] = k1 ? S[8 * u + 1] : NEG;
      S[8 * u + 2] = diag ? S[8 * u + 2] : NEG;
      S[8 * u + 3] = diag ? S[8 * u + 3] : NEG;
      S[8 * u + 4] = diag ? NEG : S[8 * u + 4];
      S[8 * u + 5] = diag ? NEG : S[8 * u + 5];
      S[8 * u + 6] = k0 ? S[8 * u + 6] : NEG;
      S[8 * u + 7] = k1 ? S[8 * u + 7] : NEG;
    }
    if (u >= lo && u <= hi) {
      x0 = fmaxf(x0, fmaxf(fmaxf(S[8 * u + 0], S[8 * u + 1]), fmaxf(S[8 * u + 4], S[8 * u + 5])));
      x1 = fmaxf(x1, fmaxf(fmaxf(S[8 * u + 2], S[8 * u + 3]), fmaxf(S[8 * u + 6], S[8 * u + 7])));
    }
  }
  x0 = fmaxf(x0, __shfl_xor_sync(~0u, x0, 1));
  x1 = fmaxf(x1, __shfl_xor_sync(~0u, x1, 1));
  x0 = fmaxf(x0, __shfl_xor_sync(~0u, x0, 2));
  x1 = fmaxf(x1, __shfl_xor_sync(~0u, x1, 2));
  {
    float a0 = ex2(m0 - x0), a1 = ex2(m1 - x1);
#pragma unroll
    for (int t = 0; t < 3; t++) {
      O[4 * t + 0] *= a0; O[4 * t + 1] *= a0;
      O[4 * t + 2] *= a1; O[4 * t + 3] *= a1;
    }
  }
  m0 = x0; m1 = x1;
#pragma unroll
  for (int u = 0; u < 4; u++) {
    if (u >= lo && u <= hi) {
      P[u][0] = pack2(ex2(S[8 * u + 0] - x0), ex2(S[8 * u + 1] - x0));
      P[u][1] = pack2(ex2(S[8 * u + 2] - x1), ex2(S[8 * u + 3] - x1));
      P[u][2] = pack2(ex2(S[8 * u + 4] - x0), ex2(S[8 * u + 5] - x0));
      P[u][3] = pack2(ex2(S[8 * u + 6] - x1), ex2(S[8 * u + 7] - x1));
    } else {
      P[u][0] = P[u][1] = P[u][2] = P[u][3] = 0u;
    }
  }
}

DEVI void att_norm(const float (&O)[12], uint32_t* res, int lane) {
  const float l0 = __shfl_sync(~0u, O[8], (lane & ~3) | 2), l1 = __shfl_sync(~0u, O[10], (lane & ~3) | 2);
  const float i0 = __fdividef(1.0f, l0), i1 = __fdividef(1.0f, l1);
#pragma unroll
  for (int t = 0; t < 3; t++) {
    res[2 * t] = pack2(O[4 * t] * i0, O[4 * t + 1] * i0);
    res[2 * t + 1] = pack2(O[4 * t + 2] * i1, O[4 * t + 3] * i1);
  }
}

DEVI int f_main_of(int f) { return f < 6 ? 224 * f + ((f & 1) ? 32 : 0) : 1344 + 192 * (f - 6); }
DEVI int f_rem_of(int f) { return f < 6 ? ((f & 1) ? 224 * f : 224 * f + 192) : 0; }
DEVI void publish_h(const TMaps& tm, uint32_t sb, int bi, int fs, int part) {
  mbar_wait(sb + OFF_BAR + 8 * (B_HS + part), 0);
  tma2_store(&tm.h, sb + OFF_A + part * 16384, fs * 192 + part * 64, bi * 128);
  if (part == 2) tma2_store(&tm.h_r, sb + OFF_A + 49152, 1536 + fs * 32, bi * 128);
  bulk_commit();
  bulk_wait0();
  mbar_arrive(sb + OFF_BAR + 8 * (B_HF + part));
  red_release(&g_flag_h[((bi * 2 + (fs >> 2)) * 4 + part) * 32]);
}

__global__ void __launch_bounds__(384, 1)
fused_block_kernel(const __grid_constant__ TMaps tm, const Params p) {
  extern __shared__ __align__(1024) uint8_t smem_raw[];
  const uint32_t sb = s2u(smem_raw);
  const int tid = threadIdx.x;
  const int lane = tid & 31;
  const int wid = __shfl_sync(~0u, tid >> 5, 0);

  uint32_t rank;
  asm volatile("mov.u32 %0, %%cluster_ctarank;" : "=r"(rank));
  int item;
  if (p.use_smid) {
    uint32_t smid;
    asm volatile("mov.u32 %0, %%smid;" : "=r"(smid));
    const int t = smid >> 1;
    int g, c;
    if (t < 32) { g = t & 7; c = t >> 3; }
    else if (t < 60) { g = 1 + (t - 32) % 7; c = 4 + (t - 32) / 7; }
    else if (t < 62) { g = -1; c = 0; }
    else { g = 0; c = 4 + (t - 62); }
    item = g < 0 ? -1 : (2 * g + (c & 1)) * 8 + (c >> 1) * 2 + (int)rank;
  } else {
    item = blockIdx.x < 128 ? (int)blockIdx.x : -1;
  }
  item = __shfl_sync(~0u, item, 0);
  if (item < 0) {
    if (tid == 0) {
      unsigned long long tk = atomicAdd(&g_ticket, 1ull);
      unsigned long long goal = (tk / NCTA + 1) * NCTA, v;
      int it = 0;
      do {
        asm volatile("ld.relaxed.gpu.global.u64 %0, [%1];" : "=l"(v) : "l"(&g_ticket) : "memory");
      } while (v < goal && ++it < SPIN_LIMIT);
    }
    return;
  }
  const int bi = item >> 3, bj = item & 7;
  const uint32_t bar = sb + OFF_BAR;
#define BAR(i) (bar + 8 * (i))
  const int pp = bj >> 1, rk = bj & 1, fs = rk * 4 + pp;
  const int f_main = f_main_of(fs), f_rem = f_rem_of(fs);
  const int n_main = 160 * pp + ((pp & 1) ? 32 : 0), n_rem = (pp & 1) ? 160 * pp : 160 * pp + 128;
#define OUT_COL(u) (rk == 0 ? n_main + 16 * (u) : (u) < 3 ? n_main + 80 + 16 * (u) : n_rem + 16 * ((u) - 3))
  const int grp1 = item < 80 ? item : -1;

  if (wid >= 8) {
    asm volatile("setmaxnreg.dec.sync.aligned.u32 72;");
    const int pw = wid & 3;
    if (pw == 0) {
      if (lane == 0) {
        init_barriers<0, 6>(bar);
        if (grp1 >= 0) {
          mbar_expect(BAR(B_SLAB), 20480);
#pragma unroll 1
          for (int m = 0; m < 4; m++) tma2(sb + OFF_SLAB + m * 5120, &tm.wmod, BAR(B_SLAB), grp1 * 16, m * 160);
        }
      }
      __syncwarp();
      bar_arrive(NB_SETUP, 384);
      if (lane == 0) {
#pragma unroll 1
        for (int kb = 0; kb < 10; kb++) {
          const int s = kb & 3;
          if (kb == 2) mbar_wait(BAR(B_SLABFREE), 0);
          if (kb >= 4) mbar_wait(BAR(B_EMPTY1 + s), ((kb >> 2) - 1) & 1);
          const uint32_t fb = BAR(B_FULL1 + s), bs = sb + OFF_B + s * SLOT_B1;
          mbar_expect(fb, 16384 + SLOT_B1);
          tma2(sb + OFF_A + s * 16384, &tm.x, fb, kb * 64, bi * 128);
          tma3(bs, &tm.wqkv_m, fb, bj * 80, kb * 64, 0);
          tma3(bs + 24576, &tm.wqkv_r, fb, bj * 80 + 64, kb * 64, 0);
        }
        l2_prefetch((const char*)p.wo + item * 6400, 6400);
        l2_prefetch((const char*)p.w1 + item * 17280, 17280);
        l2_prefetch((const char*)p.w2 + item * 17280, 17280);
        mbar_expect(BAR(B_SLAB2), 20480);
#pragma unroll 1
        for (int m = 0; m < 4; m++) tma2(sb + OFF_SLAB + m * 5120, &tm.wmod, BAR(B_SLAB2), (80 + item) * 16, m * 160);
        mbar_wait(BAR(B_QKVDONE), 0);
        const uint32_t ep1 = lds32(sb + OFF_EP);
#pragma unroll 1
        for (int t = 3; t >= 0; t--) {
          const int d = 2 - (t >> 1);
          if (bi >= d) {
            const int src = (item - 8 * d) * 2 + (t & 1);
            poll_ge(&g_flag_kv[src * 8], ep1);
            mbar_expect(BAR(B_KV + t), KV_HALF);
            bulk_load(sb + d * KV_IMG + (t & 1) * KV_HALF, &g_kv[(size_t)src * (KV_HALF / 16)], KV_HALF, BAR(B_KV + t));
          }
        }
        mbar_wait(BAR(B_SLAB2FREE), 0);
        if (item >= 96) {
          mbar_expect(BAR(B_SLAB2), 20480);
#pragma unroll 1
          for (int m = 0; m < 4; m++) tma2(sb + OFF_SLAB + m * 5120, &tm.wmod, BAR(B_SLAB2), (112 + item) * 16, m * 160);
        }
        mbar_expect(BAR(B_WOB), 8 * 10240);
#pragma unroll 1
        for (int n = 7; n >= 0; n--) {
          if (n == 3 && item >= 96) mbar_wait(BAR(B_SLAB2FREE), 1);
          tma3(sb + OFF_WO + (9 - n) * 10240, &tm.wo, BAR(B_WOB), 0, n * 64, bj * 5);
        }
        mbar_wait(BAR(B_OREL), 0);
        int m = 0;
#pragma unroll 1
        for (int n = -1; n < 20; n++) {
          if (n == 0 || n == 10) {
            poll_ge(n ? &g_flag_x1[bi * 32] : &g_flag_o[bi * 32], ep1 * 8);
            fence_async_gmem();
          }
          if (n >= 0) {
            const int s = n & 3;
            if (n >= 4) mbar_wait(BAR(B_AE + s), ((n >> 2) - 1) & 1);
            mbar_expect(BAR(B_AF + s), 16384);
            tma2(sb + OFF_A + s * 16384, n < 10 ? &tm.o : &tm.x1, BAR(B_AF + s), (n < 10 ? n : n - 10) * 64, bi * 128);
          }
          if (n == 3) {
            mbar_expect(BAR(B_WOB + 1), 2 * 10240);
            tma3(sb + OFF_WO, &tm.wo, BAR(B_WOB + 1), 0, 8 * 64, bj * 5);
            tma3(sb + OFF_WO + 10240, &tm.wo, BAR(B_WOB + 1), 0, 9 * 64, bj * 5);
          }
          const int mend = n < 5 ? 1 : n < 9 ? 2 : n < 13 ? 3 : n < 18 ? n - 8 : 10;
#pragma unroll 1
          for (; m < mend; m++) {
            const int s = m % 5;
            if (m == 3) mbar_wait(BAR(B_AE + 3), 1);
            if (m >= 5) mbar_wait(BAR(B_BE + s), 0);
            const uint32_t fb = BAR(B_BF + s), bs = sb + slot_b(s);
            mbar_expect(fb, SLOT_B);
            tma3(bs, &tm.w1_m, fb, 0, m * 64, f_main >> 6);
            tma2(bs + 24576, &tm.w1_r, fb, f_rem, m * 64);
          }
        }
        const int r0 = f_main_of(rk * 4 + (pp <= 0)), r1 = f_main_of(rk * 4 + 1 + (pp <= 1)), r2 = f_main_of(rk * 4 + 2 + (pp <= 2));
        int s5 = 0, ph = 1, ra = f_main, rb = f_main + 64, rc = f_main + 128;
#pragma unroll 1
        for (int t = 0; t < 14; t++) {
          mbar_wait(BAR(B_BE + s5), ph);
          const uint32_t fb = BAR(B_BF + s5), bs = sb + slot_b(s5);
          mbar_expect(fb, 20480);
          if (t < 12) {
            tma3(bs, &tm.w2_m, fb, 0, ra, n_main >> 6);
            tma2(bs + 16384, &tm.w2_n, fb, n_rem, ra);
            const int nx = t == 0 ? r0 : t == 1 ? r1 : t == 2 ? r2 : ra + 64;
            ra = rb; rb = rc; rc = nx;
          } else {
#pragma unroll 1
            for (int e = 0; e < 2; e++) {
              const int row = f_rem_of(rk * 4 + (t - 12) * 2 + e);
              tma2(bs + e * 4096, &tm.w2_k, fb, n_main, row);
              tma2(bs + 8192 + e * 4096, &tm.w2_k, fb, n_main + 64, row);
              tma2(bs + 16384 + e * 2048, &tm.w2_kn, fb, n_rem, row);
            }
          }
          if (t == 11) {
            mbar_expect(BAR(B_X1G), 20480);
#pragma unroll 1
            for (int u = 0; u < 5; u++) tma2(sb + slot_b(u) + 20480, &tm.x1g, BAR(B_X1G), OUT_COL(u), bi * 128);
          }
          if (++s5 == 5) { s5 = 0; ph ^= 1; }
        }
      }
    } else {
      const int t = tid - 288;
      if (t == 0) {
        unsigned long long tk = atomicAdd(&g_ticket, 1ull);
        sts32(sb + OFF_EP, (uint32_t)(tk / NCTA) + 1u);
      }
      if (t == 32) init_barriers<6, NBAR>(bar);
      __syncwarp();
      bar_sync(NB_SETUP, 384);
      const uint32_t ep1 = lds32(sb + OFF_EP);
      if (pw == 1) {
        if (lane == 0) {
          mbar_wait(BAR(B_KV + 5), 0);
          bulk_store(&g_kv[(size_t)(item * 2 + 1) * (KV_HALF / 16)], sb + KV_HALF, KV_HALF);
          bulk_commit();
          mbar_wait(BAR(B_KV + 4), 0);
          bulk_store(&g_kv[(size_t)(item * 2) * (KV_HALF / 16)], sb, KV_HALF);
          bulk_commit();
          bulk_wait1();
          red_release(&g_flag_kv[(item * 2 + 1) * 8]);
          bulk_wait0();
          red_release(&g_flag_kv[(item * 2) * 8]);
#pragma unroll 1
          for (int k = 0; k < 2; k++) {
            mbar_wait(BAR(B_OPUB + k), 0);
            red_release(k ? &g_flag_x1[bi * 32] : &g_flag_o[bi * 32]);
            if (k == 0) mbar_arrive(BAR(B_OREL));
          }
#pragma unroll 1
          for (int k = 0; k < 3; k += 2) publish_h(tm, sb, bi, fs, k);
        }
      } else {
        const int t2 = t - 32;
#pragma unroll 1
        for (int k = 0; k < (item >= 96 ? 2 : 1); k++) {
          mbar_wait(BAR(B_SLAB2), k);
          if (k) bar_sync(NB_P23, 64);
          gemv_part(sb, (pw - 2) * 320, 20, lane, sb + OFF_RED + 256 + (pw - 2) * 64);
          if (lane == 0) mbar_arrive(BAR(B_SLAB2FREE));
          __syncwarp();
          bar_sync(NB_P23, 64);
          if (pw == 2) gemv_final<2>(sb + OFF_RED + 256, 80 + item + 32 * k, lane, ep1);
          __syncwarp();
        }
#pragma unroll
        for (int k = 0; k < 4; k++) {
          const int u = t2 + 64 * k;
          if (u < 224) {
            const float v = u < 192 ? __bfloat162float(p.b1[f_main + u]) : (fs < 6 ? __bfloat162float(p.b1[f_rem + u - 192]) : 0.f);
            sts32(sb + OFF_B1T + u * 4, __float_as_uint(0.5f * v));
          }
        }
        if (t2 < 10) sts128(sb + OFF_B2 + t2 * 16, ldg_nc(p.b2 + OUT_COL(t2 >> 1) + (t2 & 1) * 8));
        mbar_wait(BAR(B_QKVDONE), 0);
        float g1 = 0.f, g2 = 0.f, gs = 0.f, s1 = 0.f, s2 = 0.f;
#pragma unroll 1
        for (int u = t2; u < 160; u += 64) {
          unsigned long long w[7];
          int it = 0;
          bool ok;
          do {
            asm volatile("ld.relaxed.gpu.global.v2.u64 {%0, %1}, [%2];" : "=l"(w[0]), "=l"(w[1]) : "l"(&g_mod[1280 + 2 * u]) : "memory");
            asm volatile("ld.relaxed.gpu.global.v2.u64 {%0, %1}, [%2];" : "=l"(w[2]), "=l"(w[3]) : "l"(&g_mod[960 + 2 * u]) : "memory");
            asm volatile("ld.relaxed.gpu.global.v2.u64 {%0, %1}, [%2];" : "=l"(w[4]), "=l"(w[5]) : "l"(&g_mod[1600 + 2 * u]) : "memory");
            asm volatile("ld.relaxed.gpu.global.u64 %0, [%1];" : "=l"(w[6]) : "l"(&g_mod[640 + 40 * bj + (u < 40 ? u : 0)]) : "memory");
            ok = true;
#pragma unroll
            for (int e = 0; e < 7; e++) ok = ok && (uint32_t)(w[e] >> 32) == ep1;
            if (!ok) __nanosleep(200);
          } while (!ok && ++it < SPIN_LIMIT);
          const uint32_t one = 0x3f803f80u, sx = (uint32_t)w[2], sy = (uint32_t)w[3];
          const uint32_t ga_ = hfma2((uint32_t)w[0], one, one), gb_ = hfma2((uint32_t)w[1], one, one);
          const int pp = (2 * u) & 7;
          const uint32_t a = sb + OFF_TAB + (u >> 2) * 64 + (pp & 3) * 16 + (pp >> 2) * 8;
          sts64(a, ga_, sx);
          sts64(a + 16, gb_, sy);
#pragma unroll
          for (int v = 0; v < 5; v++)
            if ((u >> 2) * 16 == OUT_COL(v)) sts64(sb + OFF_GB + v * 32 + (u & 3) * 8, (uint32_t)w[4], (uint32_t)w[5]);
          if (u < 40) sts64(sb + OFF_GA + (u >> 3) * 64 + (u & 3) * 16 + ((u >> 2) & 1) * 8, (uint32_t)w[6] << 16, (uint32_t)w[6] & 0xffff0000u);
          const float gg[4] = {bf_lo(ga_), bf_hi(ga_), bf_lo(gb_), bf_hi(gb_)};
          const float ss[4] = {bf_lo(sx), bf_hi(sx), bf_lo(sy), bf_hi(sy)};
#pragma unroll
          for (int e = 0; e < 4; e += 2) {
            const int pr = 2 * u + (e >> 1) - 40 * bj;
            if (pr >= 0 && pr < 40) {
              const float a0 = gg[e] * gg[e], a1 = gg[e + 1] * gg[e + 1], c0 = gg[e] * ss[e], c1 = gg[e + 1] * ss[e + 1];
              const uint32_t ah = pack2(a0, a1), ch = pack2(c0, c1);
              const uint32_t col[6] = {one, e ? gb_ : ga_, ah, pack2(a0 - bf_lo(ah), a1 - bf_hi(ah)), ch, pack2(c0 - bf_lo(ch), c1 - bf_hi(ch))};
#pragma unroll
              for (int n = 0; n < 6; n++) sts32(sb + OFF_STB + (pr >> 3) * 192 + (n * 4 + (pr & 3)) * 8 + ((pr >> 2) & 1) * 4, col[n]);
            }
          }
#pragma unroll
          for (int e = 0; e < 4; e++) {
            g1 += gg[e]; g2 = fmaf(gg[e], gg[e], g2); gs = fmaf(gg[e], ss[e], gs);
            s1 += ss[e]; s2 = fmaf(ss[e], ss[e], s2);
          }
        }
#pragma unroll
        for (int o = 16; o > 0; o >>= 1) {
          g1 += __shfl_xor_sync(~0u, g1, o); g2 += __shfl_xor_sync(~0u, g2, o); gs += __shfl_xor_sync(~0u, gs, o);
          s1 += __shfl_xor_sync(~0u, s1, o); s2 += __shfl_xor_sync(~0u, s2, o);
        }
        if (lane == 0) {
          const uint32_t a = sb + OFF_CST + (pw - 2) * 32;
          sts32(a, __float_as_uint(g1)); sts32(a + 4, __float_as_uint(g2)); sts32(a + 8, __float_as_uint(gs));
          sts32(a + 12, __float_as_uint(s1)); sts32(a + 16, __float_as_uint(s2));
        }
        __syncwarp();
        mbar_arrive(BAR(B_TAB2));
        if (pw == 2) {
          mbar_wait(BAR(B_TAB2), 0);
          mbar_wait(BAR(B_SPUB), 0);
          const int row = bj * 16 + (lane & 15), hf = lane >> 4;
          uint4 v[8];
          int it = 0;
          bool ok;
          do {
            ok = true;
#pragma unroll
            for (int e = 0; e < 8; e++) {
              v[e] = ll_load16(&g_stats[((bi * 8 + e) * 2 + hf) * 128 + row]);
              ok = ok && v[e].w == ep1;
            }
          } while (!ok && ++it < SPIN_LIMIT);
          __syncwarp();
          float sv[6];
          sv[0] = sv[1] = sv[2] = 0.f;
#pragma unroll
          for (int e = 0; e < 8; e++) {
            sv[0] += __uint_as_float(v[e].x); sv[1] += __uint_as_float(v[e].y); sv[2] += __uint_as_float(v[e].z);
          }
#pragma unroll
          for (int e = 0; e < 3; e++) sv[3 + e] = __shfl_down_sync(~0u, sv[e], 16);
          float cst[5];
#pragma unroll
          for (int e = 0; e < 5; e++) cst[e] = __uint_as_float(lds32(sb + OFF_CST + e * 4)) + __uint_as_float(lds32(sb + OFF_CST + 32 + e * 4));
          const float inv = 1.0f / DM;
          const float mu1 = sv[0] * inv;
          const float r1 = rsqrtf(fmaxf(fmaf(-mu1, mu1, sv[1] * inv), 0.f) + 1e-5f);
          const float mu2 = fmaf(r1, fmaf(-mu1, cst[0], sv[2]), cst[3]) * inv;
          const float hh = fmaf(r1 * r1, fmaf(mu1, fmaf(mu1, cst[1], -2.f * sv[3]), sv[4]),
                                fmaf(2.f * r1, fmaf(-mu1, cst[2], sv[5]), cst[4])) * inv;
          const float r2 = 0.5f * rsqrtf(fmaxf(fmaf(-mu2, mu2, hh), 0.f) + 1e-5f);
          const float ab = bf_lo(pack2(r1 * r2, 0.f) & 0xffffu);
          if (lane < 16)
            ll_store16(&g_fin[bi * 128 + row], __uint_as_float(pack2(ab, -mu1 * ab)), __uint_as_float(pack2(r2, -mu2 * r2)), 0.f, ep1);
          __syncwarp();
          if (lane == 0) { mbar_arrive(BAR(B_FIN)); }
        }
        if (pw == 2 && lane == 0) {
          int ca = (rk * 4 + (pp <= 0)) * 192, cb = (rk * 4 + 1 + (pp <= 1)) * 192, cc = (rk * 4 + 2 + (pp <= 2)) * 192;
#pragma unroll 1
          for (int t = 0; t < 11; t++) {
            const int s = t & 3;
            if (t < 3) mbar_wait(BAR(B_HF + t), 0);
            if (t == 0 || t == 3 || t == 6) {
              poll_ge(&g_flag_h[((bi * 2 + rk) * 4 + t / 3) * 32], ep1 * 4);
            }
            if (t >= 4) mbar_wait(BAR(B_AE + s), (t >> 2) & 1);
            mbar_expect(BAR(B_AF + s), 16384);
            tma2(sb + OFF_A + s * 16384, &tm.h, BAR(B_AF + s), t < 9 ? ca : 1536 + rk * 128 + (t - 9) * 64, bi * 128);
            const int nx = ca + 64;
            ca = cb; cb = cc; cc = nx;
          }
        }
        if (pw == 3 && lane == 0) {
          mbar_expect(BAR(B_RX), 10240);
          mbar_expect(BAR(B_RX + 1), 10240);
          publish_h(tm, sb, bi, fs, 1);
        }
      }
    }
  } else {
    asm volatile("setmaxnreg.inc.sync.aligned.u32 216;");
    const int wg = wid >> 2, w = wid & 3;
    const int g = lane >> 2, q = lane & 3;
    const int wr = wg ? 3 - w : w;
    uint32_t ep1;
    uint32_t ra0, rc0, ra1, rc1;
    {
      if (wg == 0) {
        if (tid < 80) {
          const uint4 cv = ldg_nc(p.c + tid * 8);
          sts128(sb + OFF_C + tid * 16, make_uint4(pack2(silu_f(bf_lo(cv.x)), silu_f(bf_hi(cv.x))), pack2(silu_f(bf_lo(cv.y)), silu_f(bf_hi(cv.y))),
                                                   pack2(silu_f(bf_lo(cv.z)), silu_f(bf_hi(cv.z))), pack2(silu_f(bf_lo(cv.w)), silu_f(bf_hi(cv.w)))));
        }
        __syncwarp();
        bar_sync(NB_SETUP, 384);
        ep1 = lds32(sb + OFF_EP);
        if (grp1 >= 0) {
          mbar_wait(BAR(B_SLAB), 0);
          gemv_part(sb, w * 160, 10, lane, sb + OFF_RED + w * 64);
          if (w == 0) {
            bar_sync(NB_GEMV, 128);
            gemv_final<4>(sb + OFF_RED, grp1, lane, ep1);
            __syncwarp();
          } else {
            bar_arrive(NB_GEMV, 128);
          }
        }
      } else {
        const int row = bi * 128 + bj * 16 + 4 * w + (lane >> 3);
        uint4 xv[10];
#pragma unroll
        for (int m = 0; m < 10; m++) xv[m] = ldg_nc(p.x + (size_t)row * DM + ((lane & 7) + 8 * m) * 8);
        bar_sync(NB_SETUP, 384);
        ep1 = lds32(sb + OFF_EP);
        float s0 = 0.f, s1 = 0.f, v0 = 0.f, v1 = 0.f;
#pragma unroll
        for (int m = 0; m < 10; m++) {
          const uint32_t u4[4] = {xv[m].x, xv[m].y, xv[m].z, xv[m].w};
#pragma unroll
          for (int e = 0; e < 4; e++) {
            const float lo = bf_lo(u4[e]), hi = bf_hi(u4[e]);
            s0 += lo; s1 += hi; v0 = fmaf(lo, lo, v0); v1 = fmaf(hi, hi, v1);
          }
        }
        s0 += s1; v0 += v1;
#pragma unroll
        for (int o = 4; o > 0; o >>= 1) { s0 += __shfl_xor_sync(~0u, s0, o); v0 += __shfl_xor_sync(~0u, v0, o); }
        const float mean = s0 * (1.0f / DM);
        const float rstd = rsqrtf(fmaxf(fmaf(-mean, mean, v0 * (1.0f / DM)), 0.f) + 1e-5f);
        const float rb = bf_lo(pack2(rstd, 0.f) & 0xffffu);
        if ((lane & 7) == 0) ll_store(&g_st1[row], pack2(rb, -mean * rb), ep1);
        __syncwarp();
      }
      const int r0 = bi * 128 + wg * 64 + wr * 16 + g;
      const int mu = tid < 160 ? tid : 0;
      unsigned long long v0, v1, c0, c1, s0, s1;
      {
        int it = 0;
        bool ok;
        do {
          asm volatile("ld.relaxed.gpu.global.v2.u64 {%0, %1}, [%2];" : "=l"(c0), "=l"(c1) : "l"(&g_mod[320 + 2 * mu]) : "memory");
          asm volatile("ld.relaxed.gpu.global.v2.u64 {%0, %1}, [%2];" : "=l"(s0), "=l"(s1) : "l"(&g_mod[2 * mu]) : "memory");
          asm volatile("ld.relaxed.gpu.global.u64 %0, [%1];" : "=l"(v0) : "l"(&g_st1[r0]) : "memory");
          asm volatile("ld.relaxed.gpu.global.u64 %0, [%1];" : "=l"(v1) : "l"(&g_st1[r0 + 8]) : "memory");
          ok = (uint32_t)(c0 >> 32) == ep1 && (uint32_t)(c1 >> 32) == ep1 && (uint32_t)(s0 >> 32) == ep1 && (uint32_t)(s1 >> 32) == ep1 &&
               (uint32_t)(v0 >> 32) == ep1 && (uint32_t)(v1 >> 32) == ep1;
        } while (!ok && ++it < SPIN_LIMIT);
      }
      __syncwarp();
      if (lane == 0) mbar_arrive(BAR(B_SLABFREE));
      if (tid < 160) {
        const uint32_t one = 0x3f803f80u;
        const int pp = (2 * tid) & 7;
        const uint32_t a = sb + OFF_TAB + (tid >> 2) * 64 + (pp & 3) * 16 + (pp >> 2) * 8;
        sts64(a, hfma2((uint32_t)c0, one, one), (uint32_t)s0);
        sts64(a + 16, hfma2((uint32_t)c1, one, one), (uint32_t)s1);
      }
      const uint32_t t0 = (uint32_t)v0, t1 = (uint32_t)v1;
      ra0 = __byte_perm(t0, 0, 0x1010); rc0 = __byte_perm(t0, 0, 0x3232);
      ra1 = __byte_perm(t1, 0, 0x1010); rc1 = __byte_perm(t1, 0, 0x3232);
      __syncwarp();
      bar_sync(NB_CONS, 256);
    }
    const int arow = wg * 64 + wr * 16 + (lane & 15);
    const uint32_t a_off = arow * 128;
    const int a_hx = lane >> 4, a_rx = arow & 7;
    uint32_t qm[4][2][4];
    {
      float accM[96], accR[24];
      uint32_t af[2][4], raw[2][4];
      uint4 pr[2];
      const uint32_t tab = sb + OFF_TAB + q * 16;
      mbar_wait(BAR(B_FULL1), 0);
#pragma unroll
      for (int kk = 0; kk < 2; kk++) {
        ldsm4(raw[kk], sb + OFF_A + a_off + (((2 * kk + a_hx) ^ a_rx) << 4));
        pr[kk] = lds128(tab + kk * 64);
      }
#pragma unroll 1
      for (int kb = 0; kb < 10; kb++) {
        const int s = kb & 3, sn = (kb + 1) & 3;
        const uint32_t bm = dlo(sb + OFF_B + s * SLOT_B1, 8192), br = dlo(sb + OFF_B + s * SLOT_B1 + 24576, 2048);
#pragma unroll
        for (int kk = 0; kk < 4; kk++) {
          const int e = kk & 1;
          af[e][0] = hfma2(hfma2(raw[e][0], ra0, rc0), pr[e].x, pr[e].y);
          af[e][1] = hfma2(hfma2(raw[e][1], ra1, rc1), pr[e].x, pr[e].y);
          af[e][2] = hfma2(hfma2(raw[e][2], ra0, rc0), pr[e].z, pr[e].w);
          af[e][3] = hfma2(hfma2(raw[e][3], ra1, rc1), pr[e].z, pr[e].w);
          WG_FENCE();
          wgmma_rs_n48_t1(accR, af[e], mkdesc(br, kk * 512, 256, 3), (kb | kk) != 0);
          wgmma_rs_n192_t1(accM, af[e], mkdesc(bm, kk * 2048, 1024, 1), (kb | kk) != 0);
          WG_COMMIT();
          if (kk < 2 || kb < 9) {
            if (kk == 2) mbar_wait(BAR(B_FULL1 + sn), ((kb + 1) >> 2) & 1);
            ldsm4(raw[e], sb + OFF_A + (kk < 2 ? s : sn) * 16384 + a_off + (((2 * ((kk + 2) & 3) + a_hx) ^ a_rx) << 4));
            pr[e] = lds128(tab + (kb * 4 + kk + 2) * 64);
          }
          WG_WAIT(1);
          if (kk == 0 && kb > 0 && lane == 0) mbar_arrive(BAR(B_EMPTY1 + ((kb - 1) & 3)));
        }
      }
      WG_WAIT(0);
      if (lane == 0) mbar_arrive(BAR(B_QKVDONE));
      __syncwarp();
      bar_sync(NB_CONS, 256);
      {
        const int r = lane & 7;
        const uint32_t ka = sb + (wg * 8 + wr * 2 + ((lane >> 3) & 1)) * KV_ATOM + r * 32 + (((lane >> 4) ^ (r >> 2)) << 4);
#pragma unroll
        for (int u = 0; u < 4; u++)
          stsm4(ka + u * 256, pack2(accM[32 + 8 * u], accM[33 + 8 * u]), pack2(accM[34 + 8 * u], accM[35 + 8 * u]),
                pack2(accM[36 + 8 * u], accM[37 + 8 * u]), pack2(accM[38 + 8 * u], accM[39 + 8 * u]));
        stsm4(ka + 4 * 256, pack2(accR[8], accR[9]), pack2(accR[10], accR[11]), pack2(accR[12], accR[13]), pack2(accR[14], accR[15]));
        const uint32_t va = sb + (wg * 8 + wr * 2) * KV_ATOM + 1280 + g * 16;
#pragma unroll
        for (int t = 0; t < 10; t++) {
          const int cA = 8 * t, cB = 8 * t + 4;
          const int offA = (cA / 20) * 384 + ((cA % 20) >> 3) * 128 + ((cA % 20) & 7) * 2;
          const int offB = (cB / 20) * 384 + ((cB % 20) >> 3) * 128 + ((cB % 20) & 7) * 2;
          const uint32_t a = va + (q < 2 ? offA : offB) + (q & 1) * 4;
          const float* src = t < 8 ? &accM[64 + 4 * t] : &accR[16 + 4 * (t - 8)];
          sts32(a, pack2(src[0], src[1]));
          sts32(a + KV_ATOM, pack2(src[2], src[3]));
        }
        sts64(va + q * 384 + 256 + 8, 0x00003f80u, 0u);
        sts64(va + q * 384 + 256 + 8 + KV_ATOM, 0x00003f80u, 0u);
        fence_async_smem();
        mbar_arrive(BAR(B_KV + 4 + wg));
      }
      {
        const float sc = 0.22360679774997896f * 1.4426950408889634f;
        uint32_t qf[5][4];
#pragma unroll
        for (int u = 0; u < 5; u++) {
          const float* src = u < 4 ? &accM[8 * u] : &accR[0];
#pragma unroll
          for (int e = 0; e < 4; e++) qf[u][e] = pack2(src[2 * e] * sc, src[2 * e + 1] * sc);
        }
#pragma unroll
        for (int h = 0; h < 4; h++)
#pragma unroll
          for (int ks = 0; ks < 2; ks++)
#pragma unroll
            for (int e = 0; e < 4; e++) {
              const int lcA = 16 * ks + (e >> 1) * 8, lcB = lcA + 4;
              const bool vA = lcA >= 4 * h && lcA < 4 * h + 20, vB = lcB >= 4 * h && lcB < 4 * h + 20;
              qm[h][ks][e] = (q < 2 ? vA : vB) ? qf[h + ks][e] : 0u;
              asm volatile("" : "+r"(qm[h][ks][e]));
            }
      }
    }
    {
      float O[4][12];
#pragma unroll
      for (int h = 0; h < 4; h++)
#pragma unroll
        for (int e = 0; e < 12; e++) O[h][e] = 0.f;
      const bool p0 = 2 * q <= g, p1 = 2 * q + 1 <= g;
      const uint32_t tri = (p0 ? 0xffffu : 0u) | (p1 ? 0xffff0000u : 0u);
      const int smin = bi >= 2 ? 0 : (bi == 1 ? 2 - wg : 4 - wg);
#pragma unroll 1
      for (int s = 4; s >= smin; s--) {
        const int t = wg + s;
        mbar_wait(BAR(B_KV + t), 0);
        const uint32_t kv = dlo(sb + (2 - (t >> 1)) * KV_IMG + (t & 1) * KV_HALF, KV_ATOM);
        uint32_t m[4][3];
#pragma unroll
        for (int u = 0; u < 4; u++) {
          const uint32_t inv = s == 0 ? ~0u : 0u, edge = (s == 4 || s == 0) ? ~0u : 0u;
          m[u][0] = ((u < wr ? ~0u : u == wr ? tri : 0u) ^ inv) | ~edge;
          m[u][1] = ((u <= wr ? ~0u : 0u) ^ inv) | ~edge;
          m[u][2] = ((u < wr ? ~0u : 0u) ^ inv) | ~edge;
        }
        att_fast_piece(O, qm, kv, m);
      }
      uint32_t redo;
      {
        float z = 0.f;
        bool ok = true;
#pragma unroll
        for (int h = 0; h < 4; h++) {
#pragma unroll
          for (int e = 0; e < 12; e++) z = fmaf(O[h][e], 0.f, z);
          ok = ok && (q != 2 || (O[h][8] >= 8.67e-19f && O[h][10] >= 8.67e-19f));
        }
        ok = ok && z == 0.f;
        asm volatile("{\n.reg .pred p, r;\nsetp.eq.u32 p, %1, 0;\nbar.red.or.pred r, %2, 128, p;\nselp.u32 %0, 1, 0, r;\n}"
                     : "=r"(redo) : "r"((uint32_t)ok), "r"(NB_VOTE + wg) : "memory");
      }
      uint32_t res[24];
      if (redo) {
        uint32_t tmp[24];
#pragma unroll 1
        for (int h = 0; h < 4; h++) {
          uint32_t qh[4][2][4];
#pragma unroll
          for (int e = 0; e < 8; e++) {
            const uint32_t v = h == 0 ? qm[0][e >> 2][e & 3] : h == 1 ? qm[1][e >> 2][e & 3] : h == 2 ? qm[2][e >> 2][e & 3] : qm[3][e >> 2][e & 3];
            qh[0][e >> 2][e & 3] = v;
            asm volatile("" : "+r"(qh[0][e >> 2][e & 3]));
          }
          float O2[12], S0[32], m0 = __int_as_float(0xff800000), m1 = m0;
          uint32_t P0[4][4];
#pragma unroll
          for (int e = 0; e < 12; e++) O2[e] = 0.f;
#pragma unroll 1
          for (int s = 4; s >= smin; s--) {
            const int t = wg + s;
            const uint32_t kv = dlo(sb + (2 - (t >> 1)) * KV_IMG + (t & 1) * KV_HALF, KV_ATOM);
            const bool diag = s == 4;
            qk_issue<0>(S0, qh, kv + h * 16);
            WG_WAIT(0);
            softmax_slab(S0, P0, O2, m0, m1, s == 0 ? wr : 0, diag ? wr : 3, (diag || s == 0) ? wr : -1, p0 == diag, p1 == diag, diag);
            pv_issue<0>(O2, P0, kv + h * 24);
            WG_WAIT(0);
          }
          att_norm(O2, &tmp[6 * h], lane);
        }
#pragma unroll
        for (int e = 0; e < 24; e++) res[e] = tmp[e];
      } else {
#pragma unroll
        for (int h = 0; h < 4; h++) att_norm(O[h], &res[6 * h], lane);
      }
      const uint32_t stg0 = sb + (wg ? KV_HALF : 2 * KV_IMG) + w * 4096, stg1 = stg0 + 2048;
      if (redo) bar_sync(NB_VOTE + wg, 128);
#pragma unroll
      for (int h = 0; h < 4; h++)
#pragma unroll
        for (int t = 0; t < 3; t++) {
          const int c = 20 * h + 8 * t + 2 * q;
          if (t < 2 || q < 2) {
            const uint32_t a0 = c < 64 ? stg0 + g * 128 + (((c >> 3) ^ g) << 4) + (c & 7) * 2 : stg1 + g * 32 + (c - 64) * 2;
            sts32(a0, res[6 * h + 2 * t]);
            sts32(a0 + (c < 64 ? 1024 : 256), res[6 * h + 2 * t + 1]);
          }
        }
      __syncwarp();
      stage_to_global(stg0, stg1, (bf16*)g_o + (size_t)(bi * 128 + wg * 64 + wr * 16) * DM + bj * 80, lane);
      __syncwarp();
      if (lane == 0) mbar_arrive(BAR(B_OPUB));
    }
    {
      uint4 xq[5];
      float acc[40];
      mbar_wait(BAR(B_WOB), 0);
      mbar_wait(BAR(B_AF), 0);
      {
        const bf16* xs = p.x + (size_t)(bi * 128 + wg * 64 + w * 16) * DM + bj * 80;
#pragma unroll
        for (int m = 0; m < 4; m++) xq[m] = ldg_nc(xs + (m * 4 + (lane >> 3)) * DM + (lane & 7) * 8);
        xq[4] = ldg_nc(xs + (lane >> 1) * DM + 64 + (lane & 1) * 8);
      }
#pragma unroll 1
      for (int n = 0; n < 10; n++) {
        const int s = n & 3, kb = n < 8 ? 9 - n : n - 8;
        if (n == 8) mbar_wait(BAR(B_WOB + 1), 0);
        mbar_wait(BAR(B_AF + s), (n >> 2) & 1);
        const uint32_t as = dlo(sb + OFF_A + s * 16384 + wg * 8192, 16), bs = dlo(sb + OFF_WO + kb * 10240, 2048);
        WG_FENCE();
#pragma unroll
        for (int kk = 0; kk < 4; kk++)
          wgmma_ss_n80_t1(acc, mkdesc(as, kk * 32, 1024, 1), mkdesc(bs, kk * 512, 256, 3), (n | kk) != 0);
        WG_COMMIT();
        WG_WAIT(1);
        if (n > 0 && lane == 0) mbar_arrive(BAR(B_AE + ((n - 1) & 3)));
      }
      const uint32_t stg0 = sb + OFF_A + 32768 + wg * 8192 + w * 2048, stg1 = stg0 + 16384;
      mbar_wait(BAR(B_TAB2), 0);
#pragma unroll
      for (int m = 0; m < 4; m++) {
        const int row = m * 4 + (lane >> 3);
        sts128(stg0 + row * 128 + (((lane & 7) ^ (row & 7)) << 4), xq[m]);
      }
      sts128(stg1 + lane * 16, xq[4]);
      __syncwarp();
      uint32_t xo[5][4];
      uint4 gav[5];
      uint2 stb[5];
      const int frow = (lane & 7) + ((lane >> 3) & 1) * 8, fdh = lane >> 4;
#pragma unroll
      for (int u = 0; u < 5; u++) {
        ldsm4(xo[u], u < 4 ? stg0 + frow * 128 + (((2 * u + fdh) ^ (frow & 7)) << 4) : stg1 + frow * 32 + fdh * 16);
        stb[u] = lane < 24 ? lds64(sb + OFF_STB + u * 192 + lane * 8) : make_uint2(0u, 0u);
        gav[u] = lds128(sb + OFF_GA + u * 64 + q * 16);
      }
      WG_WAIT(0);
      if (lane == 0) mbar_arrive(BAR(B_AE + 1));
#pragma unroll
      for (int u = 0; u < 5; u++) {
#pragma unroll
        for (int e = 0; e < 4; e++)
          xo[u][e] = pack2(fmaf(__uint_as_float(e < 2 ? gav[u].x : gav[u].z), acc[8 * u + 2 * e], bf_lo(xo[u][e])),
                           fmaf(__uint_as_float(e < 2 ? gav[u].y : gav[u].w), acc[8 * u + 2 * e + 1], bf_hi(xo[u][e])));
        stsm4(u < 4 ? stg0 + frow * 128 + (((2 * u + fdh) ^ (frow & 7)) << 4) : stg1 + frow * 32 + fdh * 16, xo[u][0], xo[u][1], xo[u][2], xo[u][3]);
      }
      __syncwarp();
      stage_to_global(stg0, stg1, (bf16*)g_x1 + (size_t)(bi * 128 + wg * 64 + w * 16) * DM + bj * 80, lane);
      __syncwarp();
      if (lane == 0) mbar_arrive(BAR(B_XPUB));
      {
        float dl[4] = {0.f, 0.f, 0.f, 0.f}, dq[4] = {0.f, 0.f, 0.f, 0.f}, dr[4] = {0.f, 0.f, 0.f, 0.f};
#pragma unroll
        for (int u = 0; u < 5; u++) {
          uint32_t xh[4], xl[4];
#pragma unroll
          for (int e = 0; e < 4; e++) {
            xh[e] = hmul2(xo[u][e], xo[u][e]);
            xl[e] = hfma2(xo[u][e], xo[u][e], xh[e] ^ 0x80008000u);
          }
          mma16816(dl, xo[u], stb[u].x, stb[u].y);
          mma16816(dq, xh, stb[u].x, stb[u].y);
          mma16816(dr, xl, stb[u].x, stb[u].y);
        }
        const int src = lane & ~3;
        float o3[2][3];
#pragma unroll
        for (int r = 0; r < 2; r++) {
          const float lin = q == 0 ? dl[2 * r] : dl[2 * r] + dl[2 * r + 1];
          const float sq = q == 0 ? dq[2 * r] + dr[2 * r] : (dq[2 * r] + dq[2 * r + 1]) + (dr[2 * r] + dr[2 * r + 1]);
          const float gsx = __shfl_sync(~0u, lin, src + 2);
          o3[r][0] = lin; o3[r][1] = sq; o3[r][2] = q == 0 ? dl[2 * r + 1] : gsx;
        }
        if (q < 2) {
#pragma unroll
          for (int r = 0; r < 2; r++)
            ll_store16(&g_stats[(item * 2 + q) * 128 + wg * 64 + w * 16 + g + 8 * r], o3[r][0], o3[r][1], o3[r][2], ep1);
        }
        __syncwarp();
        if (lane == 0) mbar_arrive(BAR(B_SPUB));
      }
    }
    uint32_t hfr[12][4];
    {
      float accM[96], accR[16];
#pragma unroll
      for (int t = 0; t < 28; t++) {
        const uint2 bv = lds64(sb + OFF_B1T + (8 * t + 2 * q) * 4);
        float* d = t < 24 ? &accM[4 * t] : &accR[4 * (t - 24)];
        d[0] = d[2] = __uint_as_float(bv.x);
        d[1] = d[3] = __uint_as_float(bv.y);
        asm volatile("" : "+f"(d[0]), "+f"(d[1]), "+f"(d[2]), "+f"(d[3]));
      }
      uint32_t ka[2], kb_[2], kr[2], kc[2];
      {
        const uint4* fp = &g_fin[bi * 128 + wg * 64 + wr * 16 + g];
        uint4 v0, v1;
        mbar_wait(BAR(B_FIN), 0);
        int it = 0;
        do {
          v0 = ll_load16(fp);
          v1 = ll_load16(fp + 8);
        } while ((v0.w != ep1 || v1.w != ep1) && ++it < SPIN_LIMIT);
        __syncwarp();
        ka[0] = __byte_perm(v0.x, 0, 0x1010); kb_[0] = __byte_perm(v0.x, 0, 0x3232);
        kr[0] = __byte_perm(v0.y, 0, 0x1010); kc[0] = __byte_perm(v0.y, 0, 0x3232);
        ka[1] = __byte_perm(v1.x, 0, 0x1010); kb_[1] = __byte_perm(v1.x, 0, 0x3232);
        kr[1] = __byte_perm(v1.y, 0, 0x1010); kc[1] = __byte_perm(v1.y, 0, 0x3232);
      }
      uint32_t af[2][4], raw[2][4];
      uint4 pr[2];
      const uint32_t tab = sb + OFF_TAB + q * 16;
      mbar_wait(BAR(B_BF), 0);
      mbar_wait(BAR(B_AF + 2), 0);
#pragma unroll
      for (int kk = 0; kk < 2; kk++) {
        ldsm4(raw[kk], sb + OFF_A + 2 * 16384 + a_off + (((2 * kk + a_hx) ^ a_rx) << 4));
        pr[kk] = lds128(tab + kk * 64);
      }
#pragma unroll 1
      for (int kb = 0; kb < 10; kb++) {
        const int n = 10 + kb, s = n & 3, sn = (n + 1) & 3, s5 = kb % 5;
        const uint32_t bs = dlo(sb + slot_b(s5), 8192);
#pragma unroll
        for (int kk = 0; kk < 4; kk++) {
          const int e = kk & 1;
          af[e][0] = hfma2(hfma2(raw[e][0], ka[0], kb_[0]), pr[e].x, hfma2(pr[e].y, kr[0], kc[0]));
          af[e][1] = hfma2(hfma2(raw[e][1], ka[1], kb_[1]), pr[e].x, hfma2(pr[e].y, kr[1], kc[1]));
          af[e][2] = hfma2(hfma2(raw[e][2], ka[0], kb_[0]), pr[e].z, hfma2(pr[e].w, kr[0], kc[0]));
          af[e][3] = hfma2(hfma2(raw[e][3], ka[1], kb_[1]), pr[e].z, hfma2(pr[e].w, kr[1], kc[1]));
          WG_FENCE();
          wgmma_rs_n32_t1(accR, af[e], mkdesc(bs, 24576 + kk * 1024, 512, 2), 1);
          wgmma_rs_n192_t1(accM, af[e], mkdesc(bs, kk * 2048, 1024, 1), 1);
          WG_COMMIT();
          if (kk < 2 || kb < 9) {
            if (kk == 2) {
              mbar_wait2(BAR(B_AF + sn), ((n + 1) >> 2) & 1, BAR(B_BF + (kb + 1) % 5), (kb + 1) / 5);
            }
            ldsm4(raw[e], sb + OFF_A + (kk < 2 ? s : sn) * 16384 + a_off + (((2 * ((kk + 2) & 3) + a_hx) ^ a_rx) << 4));
            pr[e] = lds128(tab + (kb * 4 + kk + 2) * 64);
          }
          WG_WAIT(1);
          if (kk == 0 && kb > 0 && lane == 0) {
            mbar_arrive(BAR(B_AE + ((n - 1) & 3)));
            mbar_arrive(BAR(B_BE + (kb + 4) % 5));
          }
        }
      }
      WG_WAIT(0);
      if (lane == 0) {
        mbar_arrive(BAR(B_AE + 3));
        mbar_arrive(BAR(B_BE + 4));
        asm volatile("{\n.reg .b32 r;\nmapa.shared::cluster.u32 r, %0, %1;\nmbarrier.arrive.relaxed.cluster.shared::cluster.b64 _, [r];\n}"
                     ::"r"(BAR(B_PEER)), "r"(rank ^ 1u) : "memory");
      }
      __syncwarp();
      bar_sync(NB_CONS, 256);
      const int srow = wg * 64 + wr * 16 + (lane & 7) + ((lane >> 3) & 1) * 8;
      uint32_t hr[2][4];
#pragma unroll
      for (int part = 0; part < 3; part++) {
#pragma unroll
        for (int s = 4 * part; s < 4 * part + 4 + 2 * (part == 2); s++) {
          const float* src = s < 12 ? &accM[8 * s] : &accR[8 * (s - 12)];
#pragma unroll
          for (int e = 0; e < 4; e++) {
            const uint32_t v = gelu_half2(src[2 * e], src[2 * e + 1]);
            if (s < 12) { hfr[s][e] = v; asm volatile("" : "+r"(hfr[s][e])); } else { hr[s - 12][e] = fs >= 6 ? 0u : v; }
          }
        }
#pragma unroll
        for (int s = 4 * part; s < 4 * part + 4; s++)
          stsm4(sb + OFF_A + part * 16384 + srow * 128 + (((2 * (s & 3) + (lane >> 4)) ^ (srow & 7)) << 4), hfr[s][0], hfr[s][1], hfr[s][2], hfr[s][3]);
        if (part == 2) {
#pragma unroll
          for (int s = 0; s < 2; s++) stsm4(sb + OFF_A + 49152 + srow * 64 + (2 * s + (lane >> 4)) * 16, hr[s][0], hr[s][1], hr[s][2], hr[s][3]);
        }
        fence_async_smem();
        __syncwarp();
        if (lane == 0) mbar_arrive(BAR(B_HS + part));

        if (part < 2) mbar_wait(BAR(B_BF + part), 0);
      }
    }
    {
      float accN[64], accS[16];
#pragma unroll
      for (int t = 0; t < 3; t++) {
        mbar_wait(BAR(B_BF + t), 0);
        const uint32_t bs = dlo(sb + slot_b(t), 8192);
        WG_FENCE();
#pragma unroll
        for (int kk = 0; kk < 4; kk++) {
          wgmma_rs_n32_t1(accS, hfr[4 * t + kk], mkdesc(bs, 16384 + kk * 1024, 512, 2), (t | kk) != 0);
          wgmma_rs_n128_t1(accN, hfr[4 * t + kk], mkdesc(bs, kk * 2048, 1024, 1), (t | kk) != 0);
        }
        WG_COMMIT();
        if (t > 0) {
          WG_WAIT(1);
          if (lane == 0) mbar_arrive(BAR(B_BE + t - 1));
        }
      }
      WG_WAIT(0);
      if (lane == 0) mbar_arrive(BAR(B_BE + 2));
      uint32_t af[4][4];
      mbar_wait2(BAR(B_AF), 1, BAR(B_BF + 3), 0);
#pragma unroll
      for (int kk = 0; kk < 2; kk++) ldsm4(af[kk], sb + OFF_A + a_off + (((2 * kk + a_hx) ^ a_rx) << 4));
#pragma unroll 1
      for (int t = 0; t < 11; t++) {
        const int n = 20 + t, s = n & 3, sn = (n + 1) & 3, m = 13 + t;
        const uint32_t bs = dlo(sb + slot_b(m % 5), 8192);
#pragma unroll
        for (int kk = 0; kk < 4; kk++) {
          WG_FENCE();
          wgmma_rs_n32_t1(accS, af[kk], mkdesc(bs, 16384 + kk * 1024, 512, 2), 1);
          wgmma_rs_n128_t1(accN, af[kk], mkdesc(bs, kk * 2048, 1024, 1), 1);
          WG_COMMIT();
          WG_WAIT(2);
          if (kk == 1 && t > 0 && lane == 0) {
            mbar_arrive(BAR(B_AE + ((n - 1) & 3)));
            mbar_arrive(BAR(B_BE + (m - 1) % 5));
          }
          if (kk < 2 || t < 10) {
            if (kk == 2) {
              mbar_wait2(BAR(B_AF + sn), ((n + 1) >> 2) & 1, BAR(B_BF + (m + 1) % 5), ((m + 1) / 5) & 1);
            }
            ldsm4(af[(kk + 2) & 3], sb + OFF_A + (kk < 2 ? s : sn) * 16384 + a_off + (((2 * ((kk + 2) & 3) + a_hx) ^ a_rx) << 4));
          }
        }
      }
      const int frow = wg * 64 + wr * 16 + (lane & 7) + ((lane >> 3) & 1) * 8;
      uint32_t xr[5][4], gbv[5][2], b2v[5][2];
      mbar_wait2(BAR(B_X1G), 0, BAR(B_PEER), 0);
#pragma unroll
      for (int u = 0; u < 5; u++) {
        ldsm4(xr[u], sb + slot_b(u) + 20480 + frow * 32 + (lane >> 4) * 16);
        gbv[u][0] = lds32(sb + OFF_GB + u * 32 + q * 4); gbv[u][1] = lds32(sb + OFF_GB + u * 32 + q * 4 + 16);
        b2v[u][0] = lds32(sb + OFF_B2 + u * 32 + q * 4); b2v[u][1] = lds32(sb + OFF_B2 + u * 32 + q * 4 + 16);
      }
      uint32_t peer;
      asm volatile("mapa.shared::cluster.u32 %0, %1, %2;" : "=r"(peer) : "r"(sb), "r"(rank ^ 1u));
      WG_WAIT(0);
      float keep[40];
#pragma unroll
      for (int u = 0; u < 5; u++) {
        uint32_t w4[4];
#pragma unroll
        for (int e = 0; e < 8; e++) {
          const float lo = accN[8 * u + e], hi = u < 3 ? accN[40 + 8 * u + e] : accS[8 * (u - 3) + e];
          keep[8 * u + e] = rk ? hi : lo;
          if (e & 1) {
            const float lo0 = accN[8 * u + e - 1], hi0 = u < 3 ? accN[40 + 8 * u + e - 1] : accS[8 * (u - 3) + e - 1];
            w4[e >> 1] = pack2(rk ? lo0 : hi0, rk ? lo : hi);
          }
        }
        asm volatile("st.async.weak.shared::cluster.mbarrier::complete_tx::bytes.v4.b32 [%0], {%1,%2,%3,%4}, [%5];"
                     ::"r"(peer + slot_b(u) + 24576 + tid * 16), "r"(w4[0]), "r"(w4[1]), "r"(w4[2]), "r"(w4[3]),
                     "r"(peer + OFF_BAR + 8 * (B_RX + wg)) : "memory");
      }
      mbar_wait(BAR(B_RX + wg), 0);
#pragma unroll
      for (int u = 0; u < 5; u++) {
        const uint4 pv = lds128(sb + slot_b(u) + 24576 + tid * 16);
        const uint32_t p4[4] = {pv.x, pv.y, pv.z, pv.w};
        uint32_t o4[4];
#pragma unroll
        for (int e = 0; e < 4; e++)
          o4[e] = pack2(fmaf(keep[8 * u + 2 * e] + bf_lo(p4[e]) + bf_lo(b2v[u][e >> 1]), bf_lo(gbv[u][e >> 1]), bf_lo(xr[u][e])),
                        fmaf(keep[8 * u + 2 * e + 1] + bf_hi(p4[e]) + bf_hi(b2v[u][e >> 1]), bf_hi(gbv[u][e >> 1]), bf_hi(xr[u][e])));
        stsm4(sb + slot_b(u) + 20480 + frow * 32 + (lane >> 4) * 16, o4[0], o4[1], o4[2], o4[3]);
      }
      __syncwarp();
      const int row0 = wg * 64 + wr * 16;
#pragma unroll
      for (int m = 0; m < 5; m++) {
        const int idx = lane + 32 * m, row = row0 + ((idx * 205) >> 11), ch = idx - ((idx * 205) >> 11) * 10;
        stg128(p.out + (size_t)(bi * 128 + row) * DM + (ch < 6 ? OUT_COL(0) : OUT_COL(3) - 48) + ch * 8,
               lds128(sb + slot_b(ch >> 1) + 20480 + row * 32 + (ch & 1) * 16));
      }
    }
  }
}

typedef CUresult (*EncodeFn)(CUtensorMap*, CUtensorMapDataType, cuuint32_t, void*, const cuuint64_t*, const cuuint64_t*,
                             const cuuint32_t*, const cuuint32_t*, CUtensorMapInterleave, CUtensorMapSwizzle,
                             CUtensorMapL2promotion, CUtensorMapFloatOOBfill);

void encode(EncodeFn fn, CUtensorMap* m, const void* base, int rank, const cuuint64_t* dims, const cuuint64_t* strides,
            const cuuint32_t* box, CUtensorMapSwizzle sw) {
  const cuuint32_t es[4] = {1, 1, 1, 1};
  fn(m, CU_TENSOR_MAP_DATA_TYPE_BFLOAT16, rank, const_cast<void*>(base), dims, strides, box, es, CU_TENSOR_MAP_INTERLEAVE_NONE, sw,
     CU_TENSOR_MAP_L2_PROMOTION_L2_128B, CU_TENSOR_MAP_FLOAT_OOB_FILL_NONE);
}

int active_clusters(int cs) {
  cudaLaunchConfig_t cfg = {};
  cfg.gridDim = dim3(cs * 16);
  cfg.blockDim = dim3(384);
  cfg.dynamicSmemBytes = SMEM_BYTES;
  cudaLaunchAttribute a[1];
  a[0].id = cudaLaunchAttributeClusterDimension;
  a[0].val.clusterDim.x = cs; a[0].val.clusterDim.y = 1; a[0].val.clusterDim.z = 1;
  cfg.attrs = a; cfg.numAttrs = 1;
  int n = 0;
  if (cudaOccupancyMaxActiveClusters(&n, fused_block_kernel, &cfg) != cudaSuccess) { (void)cudaGetLastError(); return -1; }
  return n;
}

}

extern "C" void kernel_launch(void* const* d_in, const int* in_sizes, int n_in, void* d_out, int out_size) {
  (void)in_sizes; (void)n_in; (void)out_size;
  static bool ready = false;
  static TMaps tm;
  static Params p;
  static const void* key[11];
  bool same = ready && key[10] == d_out;
  for (int i = 0; i < 10 && same; i++) same = key[i] == d_in[i];
  if (!same) {
    for (int i = 0; i < 10; i++) key[i] = d_in[i];
    key[10] = d_out;
    void* fp = nullptr;
    cudaDriverEntryPointQueryResult qr;
    cudaGetDriverEntryPoint("cuTensorMapEncodeTiled", &fp, cudaEnableDefault, &qr);
    EncodeFn fn = (EncodeFn)fp;
    void *o_ptr, *x1_ptr, *h_ptr;
    cudaGetSymbolAddress(&o_ptr, g_o);
    cudaGetSymbolAddress(&x1_ptr, g_x1);
    cudaGetSymbolAddress(&h_ptr, g_h);
    const void *x = d_in[0], *wqkv = d_in[1], *wo = d_in[2], *w1 = d_in[4], *w2 = d_in[6];
    {
      const cuuint64_t d[2] = {640, 2048}, s[1] = {1280};
      const cuuint32_t b[2] = {64, 128};
      encode(fn, &tm.x, x, 2, d, s, b, CU_TENSOR_MAP_SWIZZLE_128B);
      encode(fn, &tm.o, o_ptr, 2, d, s, b, CU_TENSOR_MAP_SWIZZLE_128B);
      encode(fn, &tm.x1, x1_ptr, 2, d, s, b, CU_TENSOR_MAP_SWIZZLE_128B);
      const cuuint32_t bg[2] = {16, 128}, br[2] = {32, 128};
      encode(fn, &tm.x1g, x1_ptr, 2, d, s, bg, CU_TENSOR_MAP_SWIZZLE_NONE);
      const cuuint64_t dh[2] = {HP, 2048}, sh[1] = {HP * 2};
      encode(fn, &tm.h, h_ptr, 2, dh, sh, b, CU_TENSOR_MAP_SWIZZLE_128B);
      encode(fn, &tm.h_r, h_ptr, 2, dh, sh, br, CU_TENSOR_MAP_SWIZZLE_NONE);
    }
    {
      const cuuint64_t d[3] = {640, 640, 3}, s[2] = {3840, 1280};
      const cuuint32_t bm[3] = {64, 64, 3}, br[3] = {16, 64, 3};
      encode(fn, &tm.wqkv_m, wqkv, 3, d, s, bm, CU_TENSOR_MAP_SWIZZLE_128B);
      encode(fn, &tm.wqkv_r, wqkv, 3, d, s, br, CU_TENSOR_MAP_SWIZZLE_32B);
    }
    {
      const cuuint64_t d[3] = {16, 640, 40}, s[2] = {1280, 32};
      const cuuint32_t b[3] = {16, 64, 5};
      encode(fn, &tm.wo, wo, 3, d, s, b, CU_TENSOR_MAP_SWIZZLE_32B);
    }
    {
      const cuuint64_t d[3] = {64, 640, 27}, s[2] = {3456, 128};
      const cuuint32_t b[3] = {64, 64, 3};
      encode(fn, &tm.w1_m, w1, 3, d, s, b, CU_TENSOR_MAP_SWIZZLE_128B);
      const cuuint64_t d2[2] = {1728, 640}, s2[1] = {3456};
      const cuuint32_t b2[2] = {32, 64};
      encode(fn, &tm.w1_r, w1, 2, d2, s2, b2, CU_TENSOR_MAP_SWIZZLE_64B);
    }
    {
      const cuuint64_t d3[3] = {64, 1728, 10}, s3[2] = {1280, 128}, d[2] = {640, 1728}, s[1] = {1280};
      const cuuint32_t bm[3] = {64, 64, 2}, bn[2] = {32, 64}, bk[2] = {64, 32}, bkn[2] = {32, 32};
      encode(fn, &tm.w2_m, w2, 3, d3, s3, bm, CU_TENSOR_MAP_SWIZZLE_128B);
      encode(fn, &tm.w2_n, w2, 2, d, s, bn, CU_TENSOR_MAP_SWIZZLE_64B);
      encode(fn, &tm.w2_k, w2, 2, d, s, bk, CU_TENSOR_MAP_SWIZZLE_128B);
      encode(fn, &tm.w2_kn, w2, 2, d, s, bkn, CU_TENSOR_MAP_SWIZZLE_64B);
    }
    {
      const cuuint64_t d[2] = {3840, 640}, s[1] = {7680};
      const cuuint32_t b[2] = {16, 160};
      encode(fn, &tm.wmod, d_in[9], 2, d, s, b, CU_TENSOR_MAP_SWIZZLE_NONE);
    }
    p.x = (const bf16*)x; p.wo = (const bf16*)wo; p.w1 = (const bf16*)w1; p.b1 = (const bf16*)d_in[5];
    p.w2 = (const bf16*)w2; p.b2 = (const bf16*)d_in[7]; p.c = (const bf16*)d_in[8];
    p.out = (bf16*)d_out;
    cudaFuncSetAttribute(fused_block_kernel, cudaFuncAttributeMaxDynamicSharedMemorySize, SMEM_BYTES);
    cudaFuncSetAttribute(fused_block_kernel, cudaFuncAttributeNonPortableClusterSizeAllowed, 1);
    int sms = 0;
    cudaDeviceGetAttribute(&sms, cudaDevAttrMultiProcessorCount, 0);
    p.use_smid = sms == NCTA && active_clusters(4) == 30 && active_clusters(8) == 15 && active_clusters(16) == 7;
    ready = true;
  }
  cudaLaunchConfig_t cfg = {};
  cfg.gridDim = dim3(NCTA);
  cfg.blockDim = dim3(384);
  cfg.dynamicSmemBytes = SMEM_BYTES;
  cfg.stream = cudaStreamPerThread;
  cudaLaunchAttribute at[1];
  at[0].id = cudaLaunchAttributeClusterDimension;
  at[0].val.clusterDim.x = 2; at[0].val.clusterDim.y = 1; at[0].val.clusterDim.z = 1;
  cfg.attrs = at; cfg.numAttrs = 1;
  cudaLaunchKernelEx(&cfg, fused_block_kernel, tm, p);
}
```

```cpp
#include <cuda_runtime.h>
#include <cuda_bf16.h>
#include <cuda.h>
#include <stdint.h>

#define DEVI __device__ __forceinline__
typedef __nv_bfloat16 bf16;

namespace {

constexpr int SEQ = 2048, DM = 640;
constexpr int HP = 1792;
constexpr int NCTA = 132;
constexpr int KV_ATOM = 2816;
constexpr int KV_HALF = 8 * KV_ATOM;
constexpr int KV_IMG = 2 * KV_HALF;
constexpr int SPIN_LIMIT = 1 << 17;

constexpr int OFF_A = 0;
constexpr int OFF_B = 65536;
constexpr int SLOT_B = 28672;
constexpr int SLOT_B1 = 30720;
constexpr int OFF_SLAB = 190464;
constexpr int OFF_C = OFF_SLAB + 20480;
constexpr int OFF_WO = 122880;
constexpr int OFF_T = 225280;
constexpr int OFF_TAB = OFF_T;
constexpr int OFF_GB = OFF_TAB + 2560;
constexpr int OFF_B1T = OFF_GB + 160;
constexpr int OFF_GA = OFF_B1T + 896;
constexpr int OFF_STB = OFF_GA + 320;
constexpr int OFF_CST = OFF_STB + 960;
constexpr int OFF_RED = OFF_CST + 64;
constexpr int OFF_B2 = OFF_RED + 384;
constexpr int OFF_BAR = OFF_B2 + 160;
constexpr int NBAR = 58;
constexpr int OFF_EP = OFF_BAR + NBAR * 8;
constexpr int SMEM_BYTES = OFF_EP + 16;
static_assert(SMEM_BYTES <= 232448, "smem");

constexpr int B_FULL1 = 0, B_SLAB = 4, B_SLABFREE = 5, B_EMPTY1 = 6, B_WOB = 10, B_AF = 12, B_AE = 16, B_BF = 20, B_BE = 25,
              B_QKVDONE = 30, B_TAB2 = 32, B_HS = 33  , B_X1G = 37, B_PEER = 38,
              B_KV = 39  , B_OPUB = 45, B_XPUB = 46, B_SLAB2 = 47, B_SLAB2FREE = 48, B_SPUB = 49,
              B_FIN = 50, B_OREL = 51, B_RX = 52  , B_HF = 55  ;
constexpr int NB_SETUP = 1, NB_CONS = 2, NB_GEMV = 5, NB_P23 = 6, NB_VOTE = 8;

struct alignas(64) TMaps {
  CUtensorMap x, wqkv_m, wqkv_r, wo, o, x1, w1_m, w1_r, wmod, h, h_r, w2_m, w2_n, w2_k, w2_kn, x1g;
};
struct Params {
  const bf16 *x, *wo, *w1, *b1, *w2, *b2, *c;
  bf16* out;
  int use_smid;
};

__device__ uint4 g_kv[128 * (KV_IMG / 16)];
__device__ uint4 g_o[SEQ * DM / 8];
__device__ uint4 g_x1[SEQ * DM / 8];
__device__ uint4 g_h[SEQ * HP / 8];
__device__ uint4 g_stats[SEQ * 8 * 2];
__device__ uint4 g_fin[SEQ];
__device__ unsigned long long g_mod[1920];
__device__ unsigned long long g_st1[SEQ];
__device__ unsigned int g_flag_kv[128 * 16];
__device__ unsigned int g_flag_o[16 * 32];
__device__ unsigned int g_flag_x1[16 * 32];
__device__ unsigned int g_flag_h[128 * 32];
__device__ unsigned long long g_ticket;
#define PSTAMP(slot) do {} while (0)
#define CSTAMP(slot) do {} while (0)
#define GSTAMP(slot) do {} while (0)
#define DSTAMP(slot, dep) do {} while (0)

DEVI uint32_t slot_b(int s) { return OFF_B + (s < 2 ? s : 6 - s) * SLOT_B; }
DEVI uint32_t s2u(const void* p) { return (uint32_t)__cvta_generic_to_shared(p); }
DEVI void mbar_init(uint32_t b, uint32_t c) { asm volatile("mbarrier.init.shared::cta.b64 [%0], %1;" ::"r"(b), "r"(c) : "memory"); }
template <int I0, int I1>
DEVI void init_barriers(uint32_t bar) {
  constexpr unsigned long long M8 = (0xfull << B_EMPTY1) | (0xfull << B_AE) | (0x1full << B_BE) | (1ull << B_QKVDONE) |
                                    (1ull << B_OPUB) | (1ull << B_XPUB) | (1ull << B_PEER) | (1ull << B_SLABFREE) |
                                    (7ull << B_HS) | (1ull << B_SPUB);
#pragma unroll
  for (int i = I0; i < I1; i++)
    mbar_init(bar + 8 * i, (M8 >> i & 1) ? 8 : i == B_KV + 4 || i == B_KV + 5 ? 128 :
                           i == B_TAB2 ? 64 : i == B_SLAB2FREE ? 2 : 1);
  asm volatile("fence.mbarrier_init.release.cluster;" ::: "memory");
}
DEVI void mbar_expect(uint32_t b, uint32_t bytes) {
  asm volatile("mbarrier.arrive.expect_tx.shared::cta.b64 _, [%0], %1;" ::"r"(b), "r"(bytes) : "memory");
}
DEVI void mbar_arrive(uint32_t b) { asm volatile("mbarrier.arrive.shared::cta.b64 _, [%0];" ::"r"(b) : "memory"); }
DEVI void mbar_wait(uint32_t b, uint32_t parity) {
  asm volatile(
      "{\n.reg .pred p;\n.reg .u32 c;\nmov.u32 c, %2;\n"
      "W: mbarrier.try_wait.parity.shared::cta.b64 p, [%0], %1;\n@p bra D;\n"
      "sub.u32 c, c, 1;\nsetp.ne.u32 p, c, 0;\n@p bra W;\nD:\n}" ::"r"(b), "r"(parity), "n"(SPIN_LIMIT) : "memory");
}
DEVI void mbar_wait2(uint32_t b0, uint32_t p0, uint32_t b1, uint32_t p1) {
  asm volatile(
      "{\n.reg .pred p, q;\n.reg .u32 c;\nmov.u32 c, %4;\n"
      "W: mbarrier.try_wait.parity.shared::cta.b64 p, [%0], %1;\n"
      "mbarrier.try_wait.parity.shared::cta.b64 q, [%2], %3;\n"
      "and.pred p, p, q;\n@p bra D;\n"
      "sub.u32 c, c, 1;\nsetp.ne.u32 p, c, 0;\n@p bra W;\nD:\n}" ::"r"(b0), "r"(p0), "r"(b1), "r"(p1), "n"(SPIN_LIMIT) : "memory");
}
DEVI void bar_sync(int id, int n) { asm volatile("bar.sync %0, %1;" ::"r"(id), "r"(n) : "memory"); }
DEVI void bar_arrive(int id, int n) { asm volatile("bar.arrive %0, %1;" ::"r"(id), "r"(n) : "memory"); }
DEVI void poll_ge(const unsigned int* p, unsigned int target) {
  unsigned int v;
  int it = 0;
  do {
    asm volatile("ld.acquire.gpu.global.u32 %0, [%1];" : "=r"(v) : "l"(p) : "memory");
  } while ((int)(v - target) < 0 && ++it < SPIN_LIMIT);
}
DEVI void red_release(unsigned int* p) { asm volatile("red.release.gpu.global.add.u32 [%0], 1;" ::"l"(p) : "memory"); }
DEVI void ll_store16(uint4* p, float a, float b, float c, uint32_t tag) {
  asm volatile("{\n.reg .b128 v;\nmov.b128 v, {%1, %2};\nst.relaxed.gpu.global.b128 [%0], v;\n}" ::"l"(p),
               "l"(((unsigned long long)__float_as_uint(b) << 32) | __float_as_uint(a)),
               "l"(((unsigned long long)tag << 32) | __float_as_uint(c)) : "memory");
}
DEVI uint4 ll_load16(const uint4* p) {
  unsigned long long a, b;
  asm volatile("{\n.reg .b128 v;\nld.relaxed.gpu.global.b128 v, [%2];\nmov.b128 {%0, %1}, v;\n}" : "=l"(a), "=l"(b) : "l"(p) : "memory");
  return make_uint4((uint32_t)a, (uint32_t)(a >> 32), (uint32_t)b, (uint32_t)(b >> 32));
}
DEVI void ll_store(unsigned long long* p, uint32_t data, uint32_t tag) {
  asm volatile("st.relaxed.gpu.global.u64 [%0], %1;" ::"l"(p), "l"(((unsigned long long)tag << 32) | data) : "memory");
}
DEVI void fence_async_gmem() { asm volatile("fence.proxy.async.global;" ::: "memory"); }
DEVI void fence_async_smem() { asm volatile("fence.proxy.async.shared::cta;" ::: "memory"); }
DEVI void tma2(uint32_t dst, const CUtensorMap* m, uint32_t bar, int c0, int c1) {
  asm volatile("cp.async.bulk.tensor.2d.shared::cluster.global.mbarrier::complete_tx::bytes [%0], [%1, {%3, %4}], [%2];"
               ::"r"(dst), "l"(m), "r"(bar), "r"(c0), "r"(c1) : "memory");
}
DEVI void tma3(uint32_t dst, const CUtensorMap* m, uint32_t bar, int c0, int c1, int c2) {
  asm volatile("cp.async.bulk.tensor.3d.shared::cluster.global.mbarrier::complete_tx::bytes [%0], [%1, {%3, %4, %5}], [%2];"
               ::"r"(dst), "l"(m), "r"(bar), "r"(c0), "r"(c1), "r"(c2) : "memory");
}
DEVI void tma2_store(const CUtensorMap* m, uint32_t src, int c0, int c1) {
  asm volatile("cp.async.bulk.tensor.2d.global.shared::cta.bulk_group [%0, {%2, %3}], [%1];" ::"l"(m), "r"(src), "r"(c0), "r"(c1) : "memory");
}
DEVI void bulk_load(uint32_t dst, const void* src, uint32_t bytes, uint32_t bar) {
  asm volatile("cp.async.bulk.shared::cluster.global.mbarrier::complete_tx::bytes [%0], [%1], %2, [%3];"
               ::"r"(dst), "l"(src), "r"(bytes), "r"(bar) : "memory");
}
DEVI void bulk_store(void* dst, uint32_t src, uint32_t bytes) {
  asm volatile("cp.async.bulk.global.shared::cta.bulk_group [%0], [%1], %2;" ::"l"(dst), "r"(src), "r"(bytes) : "memory");
}
DEVI void bulk_commit() { asm volatile("cp.async.bulk.commit_group;" ::: "memory"); }
DEVI void bulk_wait1() { asm volatile("cp.async.bulk.wait_group 1;" ::: "memory"); }
DEVI void bulk_wait0() { asm volatile("cp.async.bulk.wait_group 0;" ::: "memory"); }
DEVI void l2_prefetch(const void* p, uint32_t bytes) {
  asm volatile("cp.async.bulk.prefetch.L2.global [%0], %1;" ::"l"(p), "r"(bytes) : "memory");
}
DEVI uint32_t dlo(uint32_t addr, uint32_t lbo) { return ((addr & 0x3FFFF) >> 4) | ((lbo >> 4) << 16); }
DEVI uint64_t mkdesc(uint32_t lo, uint32_t off, uint32_t sbo, uint32_t sw) {
  return (uint64_t)(lo + (off >> 4)) | ((uint64_t)((sbo >> 4) | (sw << 30)) << 32);
}
#define WG_FENCE() asm volatile("wgmma.fence.sync.aligned;" ::: "memory")
#define WG_COMMIT() asm volatile("wgmma.commit_group.sync.aligned;" ::: "memory")
#define WG_WAIT(n) asm volatile("wgmma.wait_group.sync.aligned %0;" ::"n"(n) : "memory")
DEVI void ldsm4(uint32_t (&r)[4], uint32_t addr) {
  asm volatile("ldmatrix.sync.aligned.m8n8.x4.shared.b16 {%0,%1,%2,%3}, [%4];"
               : "=r"(r[0]), "=r"(r[1]), "=r"(r[2]), "=r"(r[3]) : "r"(addr) : "memory");
}
DEVI void ldsm4t(uint32_t (&r)[4], uint32_t addr) {
  asm volatile("ldmatrix.sync.aligned.m8n8.x4.trans.shared.b16 {%0,%1,%2,%3}, [%4];"
               : "=r"(r[0]), "=r"(r[1]), "=r"(r[2]), "=r"(r[3]) : "r"(addr) : "memory");
}
DEVI void mma_rows8(float (&d)[4], uint32_t a0, uint32_t a2, uint32_t b0, uint32_t b1) {
  asm volatile("mma.sync.aligned.m16n8k16.row.col.f32.bf16.bf16.f32 {%0,%1,%2,%3}, {%4,%5,%6,%5}, {%7,%8}, {%0,%1,%2,%3};"
               : "+f"(d[0]), "+f"(d[1]), "+f"(d[2]), "+f"(d[3]) : "r"(a0), "r"(0u), "r"(a2), "r"(b0), "r"(b1));
}
DEVI void mma16816(float (&d)[4], const uint32_t (&a)[4], uint32_t b0, uint32_t b1) {
  asm volatile("mma.sync.aligned.m16n8k16.row.col.f32.bf16.bf16.f32 {%0,%1,%2,%3}, {%4,%5,%6,%7}, {%8,%9}, {%0,%1,%2,%3};"
               : "+f"(d[0]), "+f"(d[1]), "+f"(d[2]), "+f"(d[3]) : "r"(a[0]), "r"(a[1]), "r"(a[2]), "r"(a[3]), "r"(b0), "r"(b1));
}
DEVI uint32_t hmul2(uint32_t a, uint32_t b) {
  uint32_t r;
  asm("mul.rn.bf16x2 %0, %1, %2;" : "=r"(r) : "r"(a), "r"(b));
  return r;
}
DEVI void stsm4(uint32_t addr, uint32_t a, uint32_t b, uint32_t c, uint32_t d) {
  asm volatile("stmatrix.sync.aligned.m8n8.x4.shared.b16 [%0], {%1,%2,%3,%4};" ::"r"(addr), "r"(a), "r"(b), "r"(c), "r"(d) : "memory");
}
DEVI uint4 lds128(uint32_t a) {
  uint4 v;
  asm volatile("ld.shared.v4.u32 {%0,%1,%2,%3}, [%4];" : "=r"(v.x), "=r"(v.y), "=r"(v.z), "=r"(v.w) : "r"(a) : "memory");
  return v;
}
DEVI uint2 lds64(uint32_t a) {
  uint2 v;
  asm volatile("ld.shared.v2.u32 {%0,%1}, [%2];" : "=r"(v.x), "=r"(v.y) : "r"(a) : "memory");
  return v;
}
DEVI uint32_t lds32(uint32_t a) {
  uint32_t v;
  asm volatile("ld.shared.u32 %0, [%1];" : "=r"(v) : "r"(a) : "memory");
  return v;
}
DEVI void sts32(uint32_t a, uint32_t v) { asm volatile("st.shared.u32 [%0], %1;" ::"r"(a), "r"(v) : "memory"); }
DEVI void sts64(uint32_t a, uint32_t x, uint32_t y) { asm volatile("st.shared.v2.u32 [%0], {%1,%2};" ::"r"(a), "r"(x), "r"(y) : "memory"); }
DEVI void sts128(uint32_t a, uint4 v) {
  asm volatile("st.shared.v4.u32 [%0], {%1,%2,%3,%4};" ::"r"(a), "r"(v.x), "r"(v.y), "r"(v.z), "r"(v.w) : "memory");
}
DEVI uint4 ldg_nc(const void* p) {
  uint4 v;
  asm volatile("ld.global.nc.L1::no_allocate.v4.u32 {%0,%1,%2,%3}, [%4];" : "=r"(v.x), "=r"(v.y), "=r"(v.z), "=r"(v.w) : "l"(p));
  return v;
}
DEVI uint4 ldg_cg(const void* p) {
  uint4 v;
  asm volatile("ld.global.cg.v4.u32 {%0,%1,%2,%3}, [%4];" : "=r"(v.x), "=r"(v.y), "=r"(v.z), "=r"(v.w) : "l"(p) : "memory");
  return v;
}
DEVI void stg128(void* p, uint4 v) {
  asm volatile("st.global.v4.u32 [%0], {%1,%2,%3,%4};" ::"l"(p), "r"(v.x), "r"(v.y), "r"(v.z), "r"(v.w) : "memory");
}
DEVI uint32_t pack2(float lo, float hi) {
  uint32_t r;
  asm("cvt.rn.bf16x2.f32 %0, %1, %2;" : "=r"(r) : "f"(hi), "f"(lo));
  return r;
}
DEVI float bf_lo(uint32_t v) { return __uint_as_float(v << 16); }
DEVI float bf_hi(uint32_t v) { return __uint_as_float(v & 0xffff0000u); }
DEVI uint32_t hfma2(uint32_t a, uint32_t b, uint32_t c) {
  uint32_t r;
  asm("fma.rn.bf16x2 %0, %1, %2, %3;" : "=r"(r) : "r"(a), "r"(b), "r"(c));
  return r;
}
DEVI float ex2(float x) {
  float r;
  asm("ex2.approx.ftz.f32 %0, %1;" : "=f"(r) : "f"(x));
  return r;
}
DEVI uint32_t gelu_half2(float z0, float z1) {
  const uint32_t z = pack2(z0, z1);
  uint32_t z2, u, t;
  asm("mul.rn.bf16x2 %0, %1, %1;" : "=r"(z2) : "r"(z));
  const uint32_t pl = hfma2(z2, 0x3e923e92u, 0x3fcc3fccu);
  asm("mul.rn.bf16x2 %0, %1, %2;" : "=r"(u) : "r"(z), "r"(pl));
  asm("tanh.approx.bf16x2 %0, %1;" : "=r"(t) : "r"(u));
  return hfma2(z, t, z);
}
DEVI float silu_f(float x) { return __fdividef(x, 1.0f + ex2(-1.4426950408889634f * x)); }

__device__ __forceinline__ void wgmma_rs_n192_t1(float (&d)[96], const uint32_t (&a)[4], uint64_t db, int sd) {
  asm volatile("{\n.reg .pred p;\nsetp.ne.b32 p, %101, 0;\nwgmma.mma_async.sync.aligned.m64n192k16.f32.bf16.bf16 "
    "{%0, %1, %2, %3, %4, %5, %6, %7, %8, %9, %10, %11, %12, %13, %14, %15, %16, %17, %18, %19, %20, %21, %22, %23, %24, %25, %26, %27, %28, %29, %30, %31, %32, %33, %34, %35, %36, %37, %38, %39, %40, %41, %42, %43, %44, %45, %46, %47, %48, %49, %50, %51, %52, %53, %54, %55, %56, %57, %58, %59, %60, %61, %62, %63, %64, %65, %66, %67, %68, %69, %70, %71, %72, %73, %74, %75, %76, %77, %78, %79, %80, %81, %82, %83, %84, %85, %86, %87, %88, %89, %90, %91, %92, %93, %94, %95}, {%96, %97, %98, %99}, %100, p, 1, 1, 1;\n}\n"
    : "+f"(d[0]), "+f"(d[1]), "+f"(d[2]), "+f"(d[3]), "+f"(d[4]), "+f"(d[5]), "+f"(d[6]), "+f"(d[7]), "+f"(d[8]), "+f"(d[9]), "+f"(d[10]), "+f"(d[11]), "+f"(d[12]), "+f"(d[13]), "+f"(d[14]), "+f"(d[15]), "+f"(d[16]), "+f"(d[17]), "+f"(d[18]), "+f"(d[19]), "+f"(d[20]), "+f"(d[21]), "+f"(d[22]), "+f"(d[23]), "+f"(d[24]), "+f"(d[25]), "+f"(d[26]), "+f"(d[27]), "+f"(d[28]), "+f"(d[29]), "+f"(d[30]), "+f"(d[31]), "+f"(d[32]), "+f"(d[33]), "+f"(d[34]), "+f"(d[35]), "+f"(d[36]), "+f"(d[37]), "+f"(d[38]), "+f"(d[39]), "+f"(d[40]), "+f"(d[41]), "+f"(d[42]), "+f"(d[43]), "+f"(d[44]), "+f"(d[45]), "+f"(d[46]), "+f"(d[47]), "+f"(d[48]), "+f"(d[49]), "+f"(d[50]), "+f"(d[51]), "+f"(d[52]), "+f"(d[53]), "+f"(d[54]), "+f"(d[55]), "+f"(d[56]), "+f"(d[57]), "+f"(d[58]), "+f"(d[59]), "+f"(d[60]), "+f"(d[61]), "+f"(d[62]), "+f"(d[63]), "+f"(d[64]), "+f"(d[65]), "+f"(d[66]), "+f"(d[67]), "+f"(d[68]), "+f"(d[69]), "+f"(d[70]), "+f"(d[71]), "+f"(d[72]), "+f"(d[73]), "+f"(d[74]), "+f"(d[75]), "+f"(d[76]), "+f"(d[77]), "+f"(d[78]), "+f"(d[79]), "+f"(d[80]), "+f"(d[81]), "+f"(d[82]), "+f"(d[83]), "+f"(d[84]), "+f"(d[85]), "+f"(d[86]), "+f"(d[87]), "+f"(d[88]), "+f"(d[89]), "+f"(d[90]), "+f"(d[91]), "+f"(d[92]), "+f"(d[93]), "+f"(d[94]), "+f"(d[95])
    : "r"(a[0]), "r"(a[1]), "r"(a[2]), "r"(a[3]), "l"(db), "r"(sd));
}
__device__ __forceinline__ void wgmma_rs_n48_t1(float (&d)[24], const uint32_t (&a)[4], uint64_t db, int sd) {
  asm volatile("{\n.reg .pred p;\nsetp.ne.b32 p, %29, 0;\nwgmma.mma_async.sync.aligned.m64n48k16.f32.bf16.bf16 "
    "{%0, %1, %2, %3, %4, %5, %6, %7, %8, %9, %10, %11, %12, %13, %14, %15, %16, %17, %18, %19, %20, %21, %22, %23}, {%24, %25, %26, %27}, %28, p, 1, 1, 1;\n}\n"
    : "+f"(d[0]), "+f"(d[1]), "+f"(d[2]), "+f"(d[3]), "+f"(d[4]), "+f"(d[5]), "+f"(d[6]), "+f"(d[7]), "+f"(d[8]), "+f"(d[9]), "+f"(d[10]), "+f"(d[11]), "+f"(d[12]), "+f"(d[13]), "+f"(d[14]), "+f"(d[15]), "+f"(d[16]), "+f"(d[17]), "+f"(d[18]), "+f"(d[19]), "+f"(d[20]), "+f"(d[21]), "+f"(d[22]), "+f"(d[23])
    : "r"(a[0]), "r"(a[1]), "r"(a[2]), "r"(a[3]), "l"(db), "r"(sd));
}
__device__ __forceinline__ void wgmma_rs_n64_t0(float (&d)[32], const uint32_t (&a)[4], uint64_t db, int sd) {
  asm volatile("{\n.reg .pred p;\nsetp.ne.b32 p, %37, 0;\nwgmma.mma_async.sync.aligned.m64n64k16.f32.bf16.bf16 "
    "{%0, %1, %2, %3, %4, %5, %6, %7, %8, %9, %10, %11, %12, %13, %14, %15, %16, %17, %18, %19, %20, %21, %22, %23, %24, %25, %26, %27, %28, %29, %30, %31}, {%32, %33, %34, %35}, %36, p, 1, 1, 0;\n}\n"
    : "+f"(d[0]), "+f"(d[1]), "+f"(d[2]), "+f"(d[3]), "+f"(d[4]), "+f"(d[5]), "+f"(d[6]), "+f"(d[7]), "+f"(d[8]), "+f"(d[9]), "+f"(d[10]), "+f"(d[11]), "+f"(d[12]), "+f"(d[13]), "+f"(d[14]), "+f"(d[15]), "+f"(d[16]), "+f"(d[17]), "+f"(d[18]), "+f"(d[19]), "+f"(d[20]), "+f"(d[21]), "+f"(d[22]), "+f"(d[23]), "+f"(d[24]), "+f"(d[25]), "+f"(d[26]), "+f"(d[27]), "+f"(d[28]), "+f"(d[29]), "+f"(d[30]), "+f"(d[31])
    : "r"(a[0]), "r"(a[1]), "r"(a[2]), "r"(a[3]), "l"(db), "r"(sd));
}
__device__ __forceinline__ void wgmma_rs_n24_t1(float (&d)[12], const uint32_t (&a)[4], uint64_t db, int sd) {
  asm volatile("{\n.reg .pred p;\nsetp.ne.b32 p, %17, 0;\nwgmma.mma_async.sync.aligned.m64n24k16.f32.bf16.bf16 "
    "{%0, %1, %2, %3, %4, %5, %6, %7, %8, %9, %10, %11}, {%12, %13, %14, %15}, %16, p, 1, 1, 1;\n}\n"
    : "+f"(d[0]), "+f"(d[1]), "+f"(d[2]), "+f"(d[3]), "+f"(d[4]), "+f"(d[5]), "+f"(d[6]), "+f"(d[7]), "+f"(d[8]), "+f"(d[9]), "+f"(d[10]), "+f"(d[11])
    : "r"(a[0]), "r"(a[1]), "r"(a[2]), "r"(a[3]), "l"(db), "r"(sd));
}
__device__ __forceinline__ void wgmma_ss_n80_t1(float (&d)[40], uint64_t da, uint64_t db, int sd) {
  asm volatile("{\n.reg .pred p;\nsetp.ne.b32 p, %42, 0;\nwgmma.mma_async.sync.aligned.m64n80k16.f32.bf16.bf16 "
    "{%0, %1, %2, %3, %4, %5, %6, %7, %8, %9, %10, %11, %12, %13, %14, %15, %16, %17, %18, %19, %20, %21, %22, %23, %24, %25, %26, %27, %28, %29, %30, %31, %32, %33, %34, %35, %36, %37, %38, %39}, %40, %41, p, 1, 1, 0, 1;\n}\n"
    : "+f"(d[0]), "+f"(d[1]), "+f"(d[2]), "+f"(d[3]), "+f"(d[4]), "+f"(d[5]), "+f"(d[6]), "+f"(d[7]), "+f"(d[8]), "+f"(d[9]), "+f"(d[10]), "+f"(d[11]), "+f"(d[12]), "+f"(d[13]), "+f"(d[14]), "+f"(d[15]), "+f"(d[16]), "+f"(d[17]), "+f"(d[18]), "+f"(d[19]), "+f"(d[20]), "+f"(d[21]), "+f"(d[22]), "+f"(d[23]), "+f"(d[24]), "+f"(d[25]), "+f"(d[26]), "+f"(d[27]), "+f"(d[28]), "+f"(d[29]), "+f"(d[30]), "+f"(d[31]), "+f"(d[32]), "+f"(d[33]), "+f"(d[34]), "+f"(d[35]), "+f"(d[36]), "+f"(d[37]), "+f"(d[38]), "+f"(d[39])
    : "l"(da), "l"(db), "r"(sd));
}
__device__ __forceinline__ void wgmma_rs_n32_t1(float (&d)[16], const uint32_t (&a)[4], uint64_t db, int sd) {
  asm volatile("{\n.reg .pred p;\nsetp.ne.b32 p, %21, 0;\nwgmma.mma_async.sync.aligned.m64n32k16.f32.bf16.bf16 "
    "{%0, %1, %2, %3, %4, %5, %6, %7, %8, %9, %10, %11, %12, %13, %14, %15}, {%16, %17, %18, %19}, %20, p, 1, 1, 1;\n}\n"
    : "+f"(d[0]), "+f"(d[1]), "+f"(d[2]), "+f"(d[3]), "+f"(d[4]), "+f"(d[5]), "+f"(d[6]), "+f"(d[7]), "+f"(d[8]), "+f"(d[9]), "+f"(d[10]), "+f"(d[11]), "+f"(d[12]), "+f"(d[13]), "+f"(d[14]), "+f"(d[15])
    : "r"(a[0]), "r"(a[1]), "r"(a[2]), "r"(a[3]), "l"(db), "r"(sd));
}
__device__ __forceinline__ void wgmma_rs_n128_t1(float (&d)[64], const uint32_t (&a)[4], uint64_t db, int sd) {
  asm volatile("{\n.reg .pred p;\nsetp.ne.b32 p, %69, 0;\nwgmma.mma_async.sync.aligned.m64n128k16.f32.bf16.bf16 "
    "{%0, %1, %2, %3, %4, %5, %6, %7, %8, %9, %10, %11, %12, %13, %14, %15, %16, %17, %18, %19, %20, %21, %22, %23, %24, %25, %26, %27, %28, %29, %30, %31, %32, %33, %34, %35, %36, %37, %38, %39, %40, %41, %42, %43, %44, %45, %46, %47, %48, %49, %50, %51, %52, %53, %54, %55, %56, %57, %58, %59, %60, %61, %62, %63}, {%64, %65, %66, %67}, %68, p, 1, 1, 1;\n}\n"
    : "+f"(d[0]), "+f"(d[1]), "+f"(d[2]), "+f"(d[3]), "+f"(d[4]), "+f"(d[5]), "+f"(d[6]), "+f"(d[7]), "+f"(d[8]), "+f"(d[9]), "+f"(d[10]), "+f"(d[11]), "+f"(d[12]), "+f"(d[13]), "+f"(d[14]), "+f"(d[15]), "+f"(d[16]), "+f"(d[17]), "+f"(d[18]), "+f"(d[19]), "+f"(d[20]), "+f"(d[21]), "+f"(d[22]), "+f"(d[23]), "+f"(d[24]), "+f"(d[25]), "+f"(d[26]), "+f"(d[27]), "+f"(d[28]), "+f"(d[29]), "+f"(d[30]), "+f"(d[31]), "+f"(d[32]), "+f"(d[33]), "+f"(d[34]), "+f"(d[35]), "+f"(d[36]), "+f"(d[37]), "+f"(d[38]), "+f"(d[39]), "+f"(d[40]), "+f"(d[41]), "+f"(d[42]), "+f"(d[43]), "+f"(d[44]), "+f"(d[45]), "+f"(d[46]), "+f"(d[47]), "+f"(d[48]), "+f"(d[49]), "+f"(d[50]), "+f"(d[51]), "+f"(d[52]), "+f"(d[53]), "+f"(d[54]), "+f"(d[55]), "+f"(d[56]), "+f"(d[57]), "+f"(d[58]), "+f"(d[59]), "+f"(d[60]), "+f"(d[61]), "+f"(d[62]), "+f"(d[63])
    : "r"(a[0]), "r"(a[1]), "r"(a[2]), "r"(a[3]), "l"(db), "r"(sd));
}
__device__ __forceinline__ void wgmma_rz_n64_t0(float (&d)[32], const uint32_t (&a)[4], uint64_t db) {
  asm volatile("wgmma.mma_async.sync.aligned.m64n64k16.f32.bf16.bf16 "
    "{%0, %1, %2, %3, %4, %5, %6, %7, %8, %9, %10, %11, %12, %13, %14, %15, %16, %17, %18, %19, %20, %21, %22, %23, %24, %25, %26, %27, %28, %29, %30, %31}, {%32, %33, %34, %35}, %36, 0, 1, 1, 0;\n"
    : "=f"(d[0]), "=f"(d[1]), "=f"(d[2]), "=f"(d[3]), "=f"(d[4]), "=f"(d[5]), "=f"(d[6]), "=f"(d[7]), "=f"(d[8]), "=f"(d[9]), "=f"(d[10]), "=f"(d[11]), "=f"(d[12]), "=f"(d[13]), "=f"(d[14]), "=f"(d[15]), "=f"(d[16]), "=f"(d[17]), "=f"(d[18]), "=f"(d[19]), "=f"(d[20]), "=f"(d[21]), "=f"(d[22]), "=f"(d[23]), "=f"(d[24]), "=f"(d[25]), "=f"(d[26]), "=f"(d[27]), "=f"(d[28]), "=f"(d[29]), "=f"(d[30]), "=f"(d[31])
    : "r"(a[0]), "r"(a[1]), "r"(a[2]), "r"(a[3]), "l"(db));
}

DEVI void gemv_part(uint32_t sb, int row0, int steps, int lane, uint32_t red_w) {
  float d0[4] = {0.f, 0.f, 0.f, 0.f}, d1[4] = {0.f, 0.f, 0.f, 0.f};
  const uint32_t m = lane < 4 ? ~0u : 0u;
#pragma unroll 5
  for (int k = 0; k < steps; k++) {
    uint32_t b[4];
    ldsm4t(b, sb + OFF_SLAB + (row0 + 16 * k + (lane & 15)) * 32 + (lane >> 4) * 16);
    const uint32_t ca = sb + OFF_C + (row0 + 16 * k) * 2 + (lane & 3) * 4, a0 = lds32(ca) & m, a2 = lds32(ca + 16) & m;
    mma_rows8(d0, a0, a2, b[0], b[1]);
    mma_rows8(d1, a0, a2, b[2], b[3]);
  }
  if (lane < 4) {
    sts64(red_w + lane * 8, __float_as_uint(d0[0]), __float_as_uint(d0[1]));
    sts64(red_w + 32 + lane * 8, __float_as_uint(d1[0]), __float_as_uint(d1[1]));
  }
  __syncwarp();
}
template <int NW>
DEVI void gemv_final(uint32_t red, int grp, int lane, uint32_t tag) {
  if (lane < 8) {
    float s0 = 0.f, s1 = 0.f;
#pragma unroll
    for (int w = 0; w < NW; w++) {
      uint2 v = lds64(red + w * 64 + lane * 8);
      s0 += __uint_as_float(v.x);
      s1 += __uint_as_float(v.y);
    }
    ll_store(&g_mod[grp * 8 + lane], pack2(s0, s1), tag);
  }
}

DEVI void stage_to_global(uint32_t p0, uint32_t p1, bf16* dst, int lane) {
#pragma unroll
  for (int m = 0; m < 4; m++) {
    int row = m * 4 + (lane >> 3), ch = lane & 7;
    uint4 v = lds128(p0 + row * 128 + ((ch ^ (row & 7)) << 4));
    stg128(dst + row * DM + ch * 8, v);
  }
  int row = lane >> 1, ch = lane & 1;
  uint4 v = lds128(p1 + row * 32 + ch * 16);
  stg128(dst + row * DM + 64 + ch * 8, v);
}

template <int H>
DEVI void qk_issue(float (&S)[32], const uint32_t (&qm)[4][2][4], uint32_t kv) {
  WG_FENCE();
  wgmma_rz_n64_t0(S, qm[H][0], mkdesc(kv, H * 256, KV_ATOM, 3));
  wgmma_rs_n64_t0(S, qm[H][1], mkdesc(kv, (H + 1) * 256, KV_ATOM, 3), 1);
  WG_COMMIT();
}
template <int H>
DEVI void pv_issue(float (&O)[12], const uint32_t (&P)[4][4], uint32_t kv) {
  WG_FENCE();
#pragma unroll
  for (int u = 0; u < 4; u++) wgmma_rs_n24_t1(O, P[u], mkdesc(kv, 1280 + H * 384 + u * 2 * KV_ATOM, 128, 0), 1);
  WG_COMMIT();
}
DEVI void exp_group(float* S, uint32_t (&P)[4], const uint32_t (&m)[4]) {
  asm volatile(
      "{\n.reg .pred p;\nsetp.ne.u32 p, %8, 0;\n"
      "@p ex2.approx.ftz.f32 %0, %0;\n@p ex2.approx.ftz.f32 %1, %1;\n@p ex2.approx.ftz.f32 %2, %2;\n@p ex2.approx.ftz.f32 %3, %3;\n"
      "@p ex2.approx.ftz.f32 %4, %4;\n@p ex2.approx.ftz.f32 %5, %5;\n@p ex2.approx.ftz.f32 %6, %6;\n@p ex2.approx.ftz.f32 %7, %7;\n}"
      : "+f"(S[0]), "+f"(S[1]), "+f"(S[2]), "+f"(S[3]), "+f"(S[4]), "+f"(S[5]), "+f"(S[6]), "+f"(S[7]) : "r"(m[3]));
  P[0] = pack2(S[0], S[1]) & m[0];
  P[1] = pack2(S[2], S[3]) & m[1];
  P[2] = pack2(S[4], S[5]) & m[2];
  P[3] = pack2(S[6], S[7]) & m[0];
}
template <int H, int U>
DEVI void pv_step(float (&O)[12], const uint32_t (&P)[4], uint32_t kv) {
  WG_FENCE();
  wgmma_rs_n24_t1(O, P, mkdesc(kv, 1280 + H * 384 + U * 2 * KV_ATOM, 128, 0), 1);
}
template <int H>
DEVI void att_head(float (&O)[4][12], float (&S)[32], float (&Sn)[32], uint32_t (&P)[4][4], const uint32_t (&qm)[4][2][4],
                   uint32_t kv, const uint32_t (&m)[4][4]) {
  exp_group(&S[0], P[0], m[0]);
  if constexpr (H > 0) {
    pv_step<H - 1, 3>(O[H - 1], P[3], kv);
    WG_COMMIT();
  }
  if constexpr (H < 3) qk_issue<H + 1>(Sn, qm, kv);
  if constexpr (H > 0) WG_WAIT(H < 3 ? 2 : 1);
  exp_group(&S[8], P[1], m[1]);
  pv_step<H, 0>(O[H], P[0], kv);
  exp_group(&S[16], P[2], m[2]);
  pv_step<H, 1>(O[H], P[1], kv);
  WG_COMMIT();
  if constexpr (H > 0) WG_WAIT(H < 3 ? 2 : 1);
  exp_group(&S[24], P[3], m[3]);
  pv_step<H, 2>(O[H], P[2], kv);
  WG_COMMIT();
  if constexpr (H < 3) WG_WAIT(1);
}
DEVI void att_fast_piece(float (&O)[4][12], const uint32_t (&qm)[4][2][4], uint32_t kv, const uint32_t (&m)[4][4]) {
  float S0[32], S1[32];
  uint32_t P[4][4];
  qk_issue<0>(S0, qm, kv);
  WG_WAIT(0);
  att_head<0>(O, S0, S1, P, qm, kv, m);
  att_head<1>(O, S1, S0, P, qm, kv, m);
  att_head<2>(O, S0, S1, P, qm, kv, m);
  att_head<3>(O, S1, S0, P, qm, kv, m);
  pv_step<3, 3>(O[3], P[3], kv);
  WG_COMMIT();
  WG_WAIT(0);
}
DEVI void softmax_slab(float (&S)[32], uint32_t (&P)[4][4], float (&O)[12], float& m0, float& m1, int lo, int hi,
                       int pu, bool k0, bool k1, bool diag) {
  const float NEG = __int_as_float(0xff800000);
  float x0 = m0, x1 = m1;
#pragma unroll
  for (int u = 0; u < 4; u++) {
    if (u == pu) {
      S[8 * u + 0] = k0 ? S[8 * u + 0] : NEG;
      S[8 * u + 1] = k1 ? S[8 * u + 1] : NEG;
      S[8 * u + 2] = diag ? S[8 * u + 2] : NEG;
      S[8 * u + 3] = diag ? S[8 * u + 3] : NEG;
      S[8 * u + 4] = diag ? NEG : S[8 * u + 4];
      S[8 * u + 5] = diag ? NEG : S[8 * u + 5];
      S[8 * u + 6] = k0 ? S[8 * u + 6] : NEG;
      S[8 * u + 7] = k1 ? S[8 * u + 7] : NEG;
    }
    if (u >= lo && u <= hi) {
      x0 = fmaxf(x0, fmaxf(fmaxf(S[8 * u + 0], S[8 * u + 1]), fmaxf(S[8 * u + 4], S[8 * u + 5])));
      x1 = fmaxf(x1, fmaxf(fmaxf(S[8 * u + 2], S[8 * u + 3]), fmaxf(S[8 * u + 6], S[8 * u + 7])));
    }
  }
  x0 = fmaxf(x0, __shfl_xor_sync(~0u, x0, 1));
  x1 = fmaxf(x1, __shfl_xor_sync(~0u, x1, 1));
  x0 = fmaxf(x0, __shfl_xor_sync(~0u, x0, 2));
  x1 = fmaxf(x1, __shfl_xor_sync(~0u, x1, 2));
  {
    float a0 = ex2(m0 - x0), a1 = ex2(m1 - x1);
#pragma unroll
    for (int t = 0; t < 3; t++) {
      O[4 * t + 0] *= a0; O[4 * t + 1] *= a0;
      O[4 * t + 2] *= a1; O[4 * t + 3] *= a1;
    }
  }
  m0 = x0; m1 = x1;
#pragma unroll
  for (int u = 0; u < 4; u++) {
    if (u >= lo && u <= hi) {
      P[u][0] = pack2(ex2(S[8 * u + 0] - x0), ex2(S[8 * u + 1] - x0));
      P[u][1] = pack2(ex2(S[8 * u + 2] - x1), ex2(S[8 * u + 3] - x1));
      P[u][2] = pack2(ex2(S[8 * u + 4] - x0), ex2(S[8 * u + 5] - x0));
      P[u][3] = pack2(ex2(S[8 * u + 6] - x1), ex2(S[8 * u + 7] - x1));
    } else {
      P[u][0] = P[u][1] = P[u][2] = P[u][3] = 0u;
    }
  }
}

DEVI void att_norm(const float (&O)[12], uint32_t* res, int lane) {
  const float l0 = __shfl_sync(~0u, O[8], (lane & ~3) | 2), l1 = __shfl_sync(~0u, O[10], (lane & ~3) | 2);
  const float i0 = __fdividef(1.0f, l0), i1 = __fdividef(1.0f, l1);
#pragma unroll
  for (int t = 0; t < 3; t++) {
    res[2 * t] = pack2(O[4 * t] * i0, O[4 * t + 1] * i0);
    res[2 * t + 1] = pack2(O[4 * t + 2] * i1, O[4 * t + 3] * i1);
  }
}

DEVI int f_main_of(int f) { return f < 6 ? 224 * f + ((f & 1) ? 32 : 0) : 1344 + 192 * (f - 6); }
DEVI int f_rem_of(int f) { return f < 6 ? ((f & 1) ? 224 * f : 224 * f + 192) : 0; }
DEVI void publish_h(const TMaps& tm, uint32_t sb, int bi, int fs, int part) {
  mbar_wait(sb + OFF_BAR + 8 * (B_HS + part), 0);
  PSTAMP(86 + 3 * part);
  tma2_store(&tm.h, sb + OFF_A + part * 16384, fs * 192 + part * 64, bi * 128);
  if (part == 2) tma2_store(&tm.h_r, sb + OFF_A + 49152, 1536 + fs * 32, bi * 128);
  bulk_commit();
  bulk_wait0();
  mbar_arrive(sb + OFF_BAR + 8 * (B_HF + part));
  PSTAMP(87 + 3 * part);
  red_release(&g_flag_h[((bi * 2 + (fs >> 2)) * 4 + part) * 32]);
  PSTAMP(88 + 3 * part);
}

__global__ void __launch_bounds__(384, 1)
fused_block_kernel(const __grid_constant__ TMaps tm, const Params p) {
  extern __shared__ __align__(1024) uint8_t smem_raw[];
  const uint32_t sb = s2u(smem_raw);
  const int tid = threadIdx.x;
  const int lane = tid & 31;
  const int wid = __shfl_sync(~0u, tid >> 5, 0);

  uint32_t rank;
  asm volatile("mov.u32 %0, %%cluster_ctarank;" : "=r"(rank));
  int item;
  if (p.use_smid) {
    uint32_t smid;
    asm volatile("mov.u32 %0, %%smid;" : "=r"(smid));
    const int t = smid >> 1;
    int g, c;
    if (t < 32) { g = t & 7; c = t >> 3; }
    else if (t < 60) { g = 1 + (t - 32) % 7; c = 4 + (t - 32) / 7; }
    else if (t < 62) { g = -1; c = 0; }
    else { g = 0; c = 4 + (t - 62); }
    item = g < 0 ? -1 : (2 * g + (c & 1)) * 8 + (c >> 1) * 2 + (int)rank;
  } else {
    item = blockIdx.x < 128 ? (int)blockIdx.x : -1;
  }
  item = __shfl_sync(~0u, item, 0);
  if (item < 0) {
    if (tid == 0) {
      unsigned long long tk = atomicAdd(&g_ticket, 1ull);
      unsigned long long goal = (tk / NCTA + 1) * NCTA, v;
      int it = 0;
      do {
        asm volatile("ld.relaxed.gpu.global.u64 %0, [%1];" : "=l"(v) : "l"(&g_ticket) : "memory");
      } while (v < goal && ++it < SPIN_LIMIT);
    }
    return;
  }
  const int bi = item >> 3, bj = item & 7;
  const uint32_t bar = sb + OFF_BAR;
#define BAR(i) (bar + 8 * (i))
  const int pp = bj >> 1, rk = bj & 1, fs = rk * 4 + pp;
  const int f_main = f_main_of(fs), f_rem = f_rem_of(fs);
  const int n_main = 160 * pp + ((pp & 1) ? 32 : 0), n_rem = (pp & 1) ? 160 * pp : 160 * pp + 128;
#define OUT_COL(u) (rk == 0 ? n_main + 16 * (u) : (u) < 3 ? n_main + 80 + 16 * (u) : n_rem + 16 * ((u) - 3))
  const int grp1 = item < 80 ? item : -1;

  if (wid >= 8) {
    asm volatile("setmaxnreg.dec.sync.aligned.u32 72;");
    const int pw = wid & 3;
    if (pw == 0) {
      if (lane == 0) { PSTAMP(32); GSTAMP(126); }
      if (lane == 0) {
        init_barriers<0, 6>(bar);
        PSTAMP(58);
        if (grp1 >= 0) {
          mbar_expect(BAR(B_SLAB), 20480);
#pragma unroll 1
          for (int m = 0; m < 4; m++) tma2(sb + OFF_SLAB + m * 5120, &tm.wmod, BAR(B_SLAB), grp1 * 16, m * 160);
        }
        PSTAMP(59);
      }
      __syncwarp();
      bar_arrive(NB_SETUP, 384);
      if (lane == 0) {
#pragma unroll 1
        for (int kb = 0; kb < 10; kb++) {
          const int s = kb & 3;
          if (kb == 2) mbar_wait(BAR(B_SLABFREE), 0);
          if (kb >= 4) mbar_wait(BAR(B_EMPTY1 + s), ((kb >> 2) - 1) & 1);
          const uint32_t fb = BAR(B_FULL1 + s), bs = sb + OFF_B + s * SLOT_B1;
          mbar_expect(fb, 16384 + SLOT_B1);
          tma2(sb + OFF_A + s * 16384, &tm.x, fb, kb * 64, bi * 128);
          tma3(bs, &tm.wqkv_m, fb, bj * 80, kb * 64, 0);
          tma3(bs + 24576, &tm.wqkv_r, fb, bj * 80 + 64, kb * 64, 0);
        }
        PSTAMP(44);
        l2_prefetch((const char*)p.wo + item * 6400, 6400);
        l2_prefetch((const char*)p.w1 + item * 17280, 17280);
        l2_prefetch((const char*)p.w2 + item * 17280, 17280);
        mbar_expect(BAR(B_SLAB2), 20480);
#pragma unroll 1
        for (int m = 0; m < 4; m++) tma2(sb + OFF_SLAB + m * 5120, &tm.wmod, BAR(B_SLAB2), (80 + item) * 16, m * 160);
        mbar_wait(BAR(B_QKVDONE), 0);
        const uint32_t ep1 = lds32(sb + OFF_EP);
        PSTAMP(33);
#pragma unroll 1
        for (int t = 3; t >= 0; t--) {
          const int d = 2 - (t >> 1);
          if (bi >= d) {
            const int src = (item - 8 * d) * 2 + (t & 1);
            poll_ge(&g_flag_kv[src * 8], ep1);
            PSTAMP(96 + t);
            mbar_expect(BAR(B_KV + t), KV_HALF);
            bulk_load(sb + d * KV_IMG + (t & 1) * KV_HALF, &g_kv[(size_t)src * (KV_HALF / 16)], KV_HALF, BAR(B_KV + t));
          }
        }
        PSTAMP(34);
        mbar_wait(BAR(B_SLAB2FREE), 0);
        if (item >= 96) {
          mbar_expect(BAR(B_SLAB2), 20480);
#pragma unroll 1
          for (int m = 0; m < 4; m++) tma2(sb + OFF_SLAB + m * 5120, &tm.wmod, BAR(B_SLAB2), (112 + item) * 16, m * 160);
        }
        mbar_expect(BAR(B_WOB), 8 * 10240);
#pragma unroll 1
        for (int n = 7; n >= 0; n--) {
          if (n == 3 && item >= 96) mbar_wait(BAR(B_SLAB2FREE), 1);
          tma3(sb + OFF_WO + (9 - n) * 10240, &tm.wo, BAR(B_WOB), 0, n * 64, bj * 5);
        }
        mbar_wait(BAR(B_OREL), 0);
        PSTAMP(35);
        int m = 0;
#pragma unroll 1
        for (int n = -1; n < 20; n++) {
          if (n == 0 || n == 10) {
            poll_ge(n ? &g_flag_x1[bi * 32] : &g_flag_o[bi * 32], ep1 * 8);
            fence_async_gmem();
            PSTAMP(n ? 38 : 36);
          }
          if (n >= 0) {
            const int s = n & 3;
            if (n >= 4) mbar_wait(BAR(B_AE + s), ((n >> 2) - 1) & 1);
            mbar_expect(BAR(B_AF + s), 16384);
            tma2(sb + OFF_A + s * 16384, n < 10 ? &tm.o : &tm.x1, BAR(B_AF + s), (n < 10 ? n : n - 10) * 64, bi * 128);
          }
          if (n == 3) {
            mbar_expect(BAR(B_WOB + 1), 2 * 10240);
            tma3(sb + OFF_WO, &tm.wo, BAR(B_WOB + 1), 0, 8 * 64, bj * 5);
            tma3(sb + OFF_WO + 10240, &tm.wo, BAR(B_WOB + 1), 0, 9 * 64, bj * 5);
          }
          const int mend = n < 5 ? 1 : n < 9 ? 2 : n < 13 ? 3 : n < 18 ? n - 8 : 10;
#pragma unroll 1
          for (; m < mend; m++) {
            const int s = m % 5;
            if (m == 3) mbar_wait(BAR(B_AE + 3), 1);
            if (m >= 5) mbar_wait(BAR(B_BE + s), 0);
            const uint32_t fb = BAR(B_BF + s), bs = sb + slot_b(s);
            mbar_expect(fb, SLOT_B);
            tma3(bs, &tm.w1_m, fb, 0, m * 64, f_main >> 6);
            tma2(bs + 24576, &tm.w1_r, fb, f_rem, m * 64);
          }
        }
        const int r0 = f_main_of(rk * 4 + (pp <= 0)), r1 = f_main_of(rk * 4 + 1 + (pp <= 1)), r2 = f_main_of(rk * 4 + 2 + (pp <= 2));
        int s5 = 0, ph = 1, ra = f_main, rb = f_main + 64, rc = f_main + 128;
#pragma unroll 1
        for (int t = 0; t < 14; t++) {
          mbar_wait(BAR(B_BE + s5), ph);
          const uint32_t fb = BAR(B_BF + s5), bs = sb + slot_b(s5);
          mbar_expect(fb, 20480);
          if (t < 12) {
            tma3(bs, &tm.w2_m, fb, 0, ra, n_main >> 6);
            tma2(bs + 16384, &tm.w2_n, fb, n_rem, ra);
            const int nx = t == 0 ? r0 : t == 1 ? r1 : t == 2 ? r2 : ra + 64;
            ra = rb; rb = rc; rc = nx;
          } else {
#pragma unroll 1
            for (int e = 0; e < 2; e++) {
              const int row = f_rem_of(rk * 4 + (t - 12) * 2 + e);
              tma2(bs + e * 4096, &tm.w2_k, fb, n_main, row);
              tma2(bs + 8192 + e * 4096, &tm.w2_k, fb, n_main + 64, row);
              tma2(bs + 16384 + e * 2048, &tm.w2_kn, fb, n_rem, row);
            }
          }
          if (t == 11) {
            mbar_expect(BAR(B_X1G), 20480);
#pragma unroll 1
            for (int u = 0; u < 5; u++) tma2(sb + slot_b(u) + 20480, &tm.x1g, BAR(B_X1G), OUT_COL(u), bi * 128);
          }
          if (++s5 == 5) { s5 = 0; ph ^= 1; }
        }
        GSTAMP(124);
        PSTAMP(39);
      }
    } else {
      const int t = tid - 288;
      if (t == 0) {
        unsigned long long tk = atomicAdd(&g_ticket, 1ull);
        sts32(sb + OFF_EP, (uint32_t)(tk / NCTA) + 1u);
      }
      if (t == 32) init_barriers<6, NBAR>(bar);
      __syncwarp();
      bar_sync(NB_SETUP, 384);
      const uint32_t ep1 = lds32(sb + OFF_EP);
      if (pw == 1) {
        if (lane == 0) {
          mbar_wait(BAR(B_KV + 5), 0);
          PSTAMP(40);
          bulk_store(&g_kv[(size_t)(item * 2 + 1) * (KV_HALF / 16)], sb + KV_HALF, KV_HALF);
          bulk_commit();
          mbar_wait(BAR(B_KV + 4), 0);
          bulk_store(&g_kv[(size_t)(item * 2) * (KV_HALF / 16)], sb, KV_HALF);
          bulk_commit();
          bulk_wait1();
          red_release(&g_flag_kv[(item * 2 + 1) * 8]);
          PSTAMP(41);
          bulk_wait0();
          red_release(&g_flag_kv[(item * 2) * 8]);
          PSTAMP(43);
#pragma unroll 1
          for (int k = 0; k < 2; k++) {
            mbar_wait(BAR(B_OPUB + k), 0);
            PSTAMP(48 + 2 * k);
            red_release(k ? &g_flag_x1[bi * 32] : &g_flag_o[bi * 32]);
            if (k == 0) mbar_arrive(BAR(B_OREL));
            PSTAMP(49 + 2 * k);
          }
#pragma unroll 1
          for (int k = 0; k < 3; k += 2) publish_h(tm, sb, bi, fs, k);
        }
      } else {
        const int t2 = t - 32;
#pragma unroll 1
        for (int k = 0; k < (item >= 96 ? 2 : 1); k++) {
          mbar_wait(BAR(B_SLAB2), k);
          if (k) bar_sync(NB_P23, 64);
          gemv_part(sb, (pw - 2) * 320, 20, lane, sb + OFF_RED + 256 + (pw - 2) * 64);
          if (lane == 0) mbar_arrive(BAR(B_SLAB2FREE));
          __syncwarp();
          bar_sync(NB_P23, 64);
          if (pw == 2) gemv_final<2>(sb + OFF_RED + 256, 80 + item + 32 * k, lane, ep1);
          __syncwarp();
        }
#pragma unroll
        for (int k = 0; k < 4; k++) {
          const int u = t2 + 64 * k;
          if (u < 224) {
            const float v = u < 192 ? __bfloat162float(p.b1[f_main + u]) : (fs < 6 ? __bfloat162float(p.b1[f_rem + u - 192]) : 0.f);
            sts32(sb + OFF_B1T + u * 4, __float_as_uint(0.5f * v));
          }
        }
        if (t2 < 10) sts128(sb + OFF_B2 + t2 * 16, ldg_nc(p.b2 + OUT_COL(t2 >> 1) + (t2 & 1) * 8));
        mbar_wait(BAR(B_QKVDONE), 0);
        float g1 = 0.f, g2 = 0.f, gs = 0.f, s1 = 0.f, s2 = 0.f;
#pragma unroll 1
        for (int u = t2; u < 160; u += 64) {
          unsigned long long w[7];
          int it = 0;
          bool ok;
          do {
            asm volatile("ld.relaxed.gpu.global.v2.u64 {%0, %1}, [%2];" : "=l"(w[0]), "=l"(w[1]) : "l"(&g_mod[1280 + 2 * u]) : "memory");
            asm volatile("ld.relaxed.gpu.global.v2.u64 {%0, %1}, [%2];" : "=l"(w[2]), "=l"(w[3]) : "l"(&g_mod[960 + 2 * u]) : "memory");
            asm volatile("ld.relaxed.gpu.global.v2.u64 {%0, %1}, [%2];" : "=l"(w[4]), "=l"(w[5]) : "l"(&g_mod[1600 + 2 * u]) : "memory");
            asm volatile("ld.relaxed.gpu.global.u64 %0, [%1];" : "=l"(w[6]) : "l"(&g_mod[640 + 40 * bj + (u < 40 ? u : 0)]) : "memory");
            ok = true;
#pragma unroll
            for (int e = 0; e < 7; e++) ok = ok && (uint32_t)(w[e] >> 32) == ep1;
            if (!ok) __nanosleep(200);
          } while (!ok && ++it < SPIN_LIMIT);
          const uint32_t one = 0x3f803f80u, sx = (uint32_t)w[2], sy = (uint32_t)w[3];
          const uint32_t ga_ = hfma2((uint32_t)w[0], one, one), gb_ = hfma2((uint32_t)w[1], one, one);
          const int pp = (2 * u) & 7;
          const uint32_t a = sb + OFF_TAB + (u >> 2) * 64 + (pp & 3) * 16 + (pp >> 2) * 8;
          sts64(a, ga_, sx);
          sts64(a + 16, gb_, sy);
#pragma unroll
          for (int v = 0; v < 5; v++)
            if ((u >> 2) * 16 == OUT_COL(v)) sts64(sb + OFF_GB + v * 32 + (u & 3) * 8, (uint32_t)w[4], (uint32_t)w[5]);
          if (u < 40) sts64(sb + OFF_GA + (u >> 3) * 64 + (u & 3) * 16 + ((u >> 2) & 1) * 8, (uint32_t)w[6] << 16, (uint32_t)w[6] & 0xffff0000u);
          const float gg[4] = {bf_lo(ga_), bf_hi(ga_), bf_lo(gb_), bf_hi(gb_)};
          const float ss[4] = {bf_lo(sx), bf_hi(sx), bf_lo(sy), bf_hi(sy)};
#pragma unroll
          for (int e = 0; e < 4; e += 2) {
            const int pr = 2 * u + (e >> 1) - 40 * bj;
            if (pr >= 0 && pr < 40) {
              const float a0 = gg[e] * gg[e], a1 = gg[e + 1] * gg[e + 1], c0 = gg[e] * ss[e], c1 = gg[e + 1] * ss[e + 1];
              const uint32_t ah = pack2(a0, a1), ch = pack2(c0, c1);
              const uint32_t col[6] = {one, e ? gb_ : ga_, ah, pack2(a0 - bf_lo(ah), a1 - bf_hi(ah)), ch, pack2(c0 - bf_lo(ch), c1 - bf_hi(ch))};
#pragma unroll
              for (int n = 0; n < 6; n++) sts32(sb + OFF_STB + (pr >> 3) * 192 + (n * 4 + (pr & 3)) * 8 + ((pr >> 2) & 1) * 4, col[n]);
            }
          }
#pragma unroll
          for (int e = 0; e < 4; e++) {
            g1 += gg[e]; g2 = fmaf(gg[e], gg[e], g2); gs = fmaf(gg[e], ss[e], gs);
            s1 += ss[e]; s2 = fmaf(ss[e], ss[e], s2);
          }
        }
#pragma unroll
        for (int o = 16; o > 0; o >>= 1) {
          g1 += __shfl_xor_sync(~0u, g1, o); g2 += __shfl_xor_sync(~0u, g2, o); gs += __shfl_xor_sync(~0u, gs, o);
          s1 += __shfl_xor_sync(~0u, s1, o); s2 += __shfl_xor_sync(~0u, s2, o);
        }
        if (lane == 0) {
          const uint32_t a = sb + OFF_CST + (pw - 2) * 32;
          sts32(a, __float_as_uint(g1)); sts32(a + 4, __float_as_uint(g2)); sts32(a + 8, __float_as_uint(gs));
          sts32(a + 12, __float_as_uint(s1)); sts32(a + 16, __float_as_uint(s2));
        }
        __syncwarp();
        mbar_arrive(BAR(B_TAB2));
        if (t2 == 0) PSTAMP(62);
        if (pw == 2) {
          mbar_wait(BAR(B_TAB2), 0);
          mbar_wait(BAR(B_SPUB), 0);
          const int row = bj * 16 + (lane & 15), hf = lane >> 4;
          uint4 v[8];
          int it = 0;
          bool ok;
          do {
            ok = true;
#pragma unroll
            for (int e = 0; e < 8; e++) {
              v[e] = ll_load16(&g_stats[((bi * 8 + e) * 2 + hf) * 128 + row]);
              ok = ok && v[e].w == ep1;
            }
          } while (!ok && ++it < SPIN_LIMIT);
          __syncwarp();
          float sv[6];
          sv[0] = sv[1] = sv[2] = 0.f;
#pragma unroll
          for (int e = 0; e < 8; e++) {
            sv[0] += __uint_as_float(v[e].x); sv[1] += __uint_as_float(v[e].y); sv[2] += __uint_as_float(v[e].z);
          }
#pragma unroll
          for (int e = 0; e < 3; e++) sv[3 + e] = __shfl_down_sync(~0u, sv[e], 16);
          float cst[5];
#pragma unroll
          for (int e = 0; e < 5; e++) cst[e] = __uint_as_float(lds32(sb + OFF_CST + e * 4)) + __uint_as_float(lds32(sb + OFF_CST + 32 + e * 4));
          const float inv = 1.0f / DM;
          const float mu1 = sv[0] * inv;
          const float r1 = rsqrtf(fmaxf(fmaf(-mu1, mu1, sv[1] * inv), 0.f) + 1e-5f);
          const float mu2 = fmaf(r1, fmaf(-mu1, cst[0], sv[2]), cst[3]) * inv;
          const float hh = fmaf(r1 * r1, fmaf(mu1, fmaf(mu1, cst[1], -2.f * sv[3]), sv[4]),
                                fmaf(2.f * r1, fmaf(-mu1, cst[2], sv[5]), cst[4])) * inv;
          const float r2 = 0.5f * rsqrtf(fmaxf(fmaf(-mu2, mu2, hh), 0.f) + 1e-5f);
          const float ab = bf_lo(pack2(r1 * r2, 0.f) & 0xffffu);
          if (lane < 16)
            ll_store16(&g_fin[bi * 128 + row], __uint_as_float(pack2(ab, -mu1 * ab)), __uint_as_float(pack2(r2, -mu2 * r2)), 0.f, ep1);
          __syncwarp();
          if (lane == 0) { mbar_arrive(BAR(B_FIN)); PSTAMP(55); }
        }
        if (pw == 2 && lane == 0) {
          int ca = (rk * 4 + (pp <= 0)) * 192, cb = (rk * 4 + 1 + (pp <= 1)) * 192, cc = (rk * 4 + 2 + (pp <= 2)) * 192;
#pragma unroll 1
          for (int t = 0; t < 11; t++) {
            const int s = t & 3;
            if (t < 3) mbar_wait(BAR(B_HF + t), 0);
            if (t == 0 || t == 3 || t == 6) {
              poll_ge(&g_flag_h[((bi * 2 + rk) * 4 + t / 3) * 32], ep1 * 4);
              PSTAMP(t ? 75 : 74);
            }
            if (t >= 4) mbar_wait(BAR(B_AE + s), (t >> 2) & 1);
            mbar_expect(BAR(B_AF + s), 16384);
            tma2(sb + OFF_A + s * 16384, &tm.h, BAR(B_AF + s), t < 9 ? ca : 1536 + rk * 128 + (t - 9) * 64, bi * 128);
            const int nx = ca + 64;
            ca = cb; cb = cc; cc = nx;
          }
        }
        if (pw == 3 && lane == 0) {
          mbar_expect(BAR(B_RX), 10240);
          mbar_expect(BAR(B_RX + 1), 10240);
          publish_h(tm, sb, bi, fs, 1);
        }
      }
    }
  } else {
    asm volatile("setmaxnreg.inc.sync.aligned.u32 216;");
    const int wg = wid >> 2, w = wid & 3;
    const int g = lane >> 2, q = lane & 3;
    const int wr = wg ? 3 - w : w;
    CSTAMP(0);
    uint32_t ep1;
    uint32_t ra0, rc0, ra1, rc1;
    {
      if (wg == 0) {
        if (tid < 80) {
          const uint4 cv = ldg_nc(p.c + tid * 8);
          sts128(sb + OFF_C + tid * 16, make_uint4(pack2(silu_f(bf_lo(cv.x)), silu_f(bf_hi(cv.x))), pack2(silu_f(bf_lo(cv.y)), silu_f(bf_hi(cv.y))),
                                                   pack2(silu_f(bf_lo(cv.z)), silu_f(bf_hi(cv.z))), pack2(silu_f(bf_lo(cv.w)), silu_f(bf_hi(cv.w)))));
        }
        __syncwarp();
        bar_sync(NB_SETUP, 384);
        ep1 = lds32(sb + OFF_EP);
        if (grp1 >= 0) {
          mbar_wait(BAR(B_SLAB), 0);
          DSTAMP(54, 0u);
          gemv_part(sb, w * 160, 10, lane, sb + OFF_RED + w * 64);
          if (w == 0) {
            bar_sync(NB_GEMV, 128);
            gemv_final<4>(sb + OFF_RED, grp1, lane, ep1);
            __syncwarp();
          } else {
            bar_arrive(NB_GEMV, 128);
          }
        }
      } else {
        const int row = bi * 128 + bj * 16 + 4 * w + (lane >> 3);
        uint4 xv[10];
#pragma unroll
        for (int m = 0; m < 10; m++) xv[m] = ldg_nc(p.x + (size_t)row * DM + ((lane & 7) + 8 * m) * 8);
        bar_sync(NB_SETUP, 384);
        ep1 = lds32(sb + OFF_EP);
        float s0 = 0.f, s1 = 0.f, v0 = 0.f, v1 = 0.f;
#pragma unroll
        for (int m = 0; m < 10; m++) {
          const uint32_t u4[4] = {xv[m].x, xv[m].y, xv[m].z, xv[m].w};
#pragma unroll
          for (int e = 0; e < 4; e++) {
            const float lo = bf_lo(u4[e]), hi = bf_hi(u4[e]);
            s0 += lo; s1 += hi; v0 = fmaf(lo, lo, v0); v1 = fmaf(hi, hi, v1);
          }
        }
        s0 += s1; v0 += v1;
#pragma unroll
        for (int o = 4; o > 0; o >>= 1) { s0 += __shfl_xor_sync(~0u, s0, o); v0 += __shfl_xor_sync(~0u, v0, o); }
        const float mean = s0 * (1.0f / DM);
        const float rstd = rsqrtf(fmaxf(fmaf(-mean, mean, v0 * (1.0f / DM)), 0.f) + 1e-5f);
        const float rb = bf_lo(pack2(rstd, 0.f) & 0xffffu);
        if ((lane & 7) == 0) ll_store(&g_st1[row], pack2(rb, -mean * rb), ep1);
        __syncwarp();
      }
      CSTAMP(1);
      const int r0 = bi * 128 + wg * 64 + wr * 16 + g;
      const int mu = tid < 160 ? tid : 0;
      unsigned long long v0, v1, c0, c1, s0, s1;
      {
        int it = 0;
        bool ok;
        do {
          asm volatile("ld.relaxed.gpu.global.v2.u64 {%0, %1}, [%2];" : "=l"(c0), "=l"(c1) : "l"(&g_mod[320 + 2 * mu]) : "memory");
          asm volatile("ld.relaxed.gpu.global.v2.u64 {%0, %1}, [%2];" : "=l"(s0), "=l"(s1) : "l"(&g_mod[2 * mu]) : "memory");
          asm volatile("ld.relaxed.gpu.global.u64 %0, [%1];" : "=l"(v0) : "l"(&g_st1[r0]) : "memory");
          asm volatile("ld.relaxed.gpu.global.u64 %0, [%1];" : "=l"(v1) : "l"(&g_st1[r0 + 8]) : "memory");
          ok = (uint32_t)(c0 >> 32) == ep1 && (uint32_t)(c1 >> 32) == ep1 && (uint32_t)(s0 >> 32) == ep1 && (uint32_t)(s1 >> 32) == ep1 &&
               (uint32_t)(v0 >> 32) == ep1 && (uint32_t)(v1 >> 32) == ep1;
        } while (!ok && ++it < SPIN_LIMIT);
      }
      __syncwarp();
      if (lane == 0) mbar_arrive(BAR(B_SLABFREE));
      if (tid < 160) {
        const uint32_t one = 0x3f803f80u;
        const int pp = (2 * tid) & 7;
        const uint32_t a = sb + OFF_TAB + (tid >> 2) * 64 + (pp & 3) * 16 + (pp >> 2) * 8;
        sts64(a, hfma2((uint32_t)c0, one, one), (uint32_t)s0);
        sts64(a + 16, hfma2((uint32_t)c1, one, one), (uint32_t)s1);
      }
      const uint32_t t0 = (uint32_t)v0, t1 = (uint32_t)v1;
      ra0 = __byte_perm(t0, 0, 0x1010); rc0 = __byte_perm(t0, 0, 0x3232);
      ra1 = __byte_perm(t1, 0, 0x1010); rc1 = __byte_perm(t1, 0, 0x3232);
      __syncwarp();
      bar_sync(NB_CONS, 256);
    }
    CSTAMP(2);
    const int arow = wg * 64 + wr * 16 + (lane & 15);
    const uint32_t a_off = arow * 128;
    const int a_hx = lane >> 4, a_rx = arow & 7;
    uint32_t qm[4][2][4];
    {
      float accM[96], accR[24];
      uint32_t af[2][4], raw[2][4];
      uint4 pr[2];
      const uint32_t tab = sb + OFF_TAB + q * 16;
      mbar_wait(BAR(B_FULL1), 0);
#pragma unroll
      for (int kk = 0; kk < 2; kk++) {
        ldsm4(raw[kk], sb + OFF_A + a_off + (((2 * kk + a_hx) ^ a_rx) << 4));
        pr[kk] = lds128(tab + kk * 64);
      }
#pragma unroll 1
      for (int kb = 0; kb < 10; kb++) {
        const int s = kb & 3, sn = (kb + 1) & 3;
        if (tid == 0) PSTAMP(64 + kb);
        const uint32_t bm = dlo(sb + OFF_B + s * SLOT_B1, 8192), br = dlo(sb + OFF_B + s * SLOT_B1 + 24576, 2048);
#pragma unroll
        for (int kk = 0; kk < 4; kk++) {
          const int e = kk & 1;
          af[e][0] = hfma2(hfma2(raw[e][0], ra0, rc0), pr[e].x, pr[e].y);
          af[e][1] = hfma2(hfma2(raw[e][1], ra1, rc1), pr[e].x, pr[e].y);
          af[e][2] = hfma2(hfma2(raw[e][2], ra0, rc0), pr[e].z, pr[e].w);
          af[e][3] = hfma2(hfma2(raw[e][3], ra1, rc1), pr[e].z, pr[e].w);
          WG_FENCE();
          wgmma_rs_n48_t1(accR, af[e], mkdesc(br, kk * 512, 256, 3), (kb | kk) != 0);
          wgmma_rs_n192_t1(accM, af[e], mkdesc(bm, kk * 2048, 1024, 1), (kb | kk) != 0);
          WG_COMMIT();
          if (kk < 2 || kb < 9) {
            if (kk == 2) mbar_wait(BAR(B_FULL1 + sn), ((kb + 1) >> 2) & 1);
            ldsm4(raw[e], sb + OFF_A + (kk < 2 ? s : sn) * 16384 + a_off + (((2 * ((kk + 2) & 3) + a_hx) ^ a_rx) << 4));
            pr[e] = lds128(tab + (kb * 4 + kk + 2) * 64);
          }
          WG_WAIT(1);
          if (kk == 0 && kb > 0 && lane == 0) mbar_arrive(BAR(B_EMPTY1 + ((kb - 1) & 3)));
        }
      }
      WG_WAIT(0);
      CSTAMP(3);
      if (lane == 0) mbar_arrive(BAR(B_QKVDONE));
      __syncwarp();
      bar_sync(NB_CONS, 256);
      {
        const int r = lane & 7;
        const uint32_t ka = sb + (wg * 8 + wr * 2 + ((lane >> 3) & 1)) * KV_ATOM + r * 32 + (((lane >> 4) ^ (r >> 2)) << 4);
#pragma unroll
        for (int u = 0; u < 4; u++)
          stsm4(ka + u * 256, pack2(accM[32 + 8 * u], accM[33 + 8 * u]), pack2(accM[34 + 8 * u], accM[35 + 8 * u]),
                pack2(accM[36 + 8 * u], accM[37 + 8 * u]), pack2(accM[38 + 8 * u], accM[39 + 8 * u]));
        stsm4(ka + 4 * 256, pack2(accR[8], accR[9]), pack2(accR[10], accR[11]), pack2(accR[12], accR[13]), pack2(accR[14], accR[15]));
        const uint32_t va = sb + (wg * 8 + wr * 2) * KV_ATOM + 1280 + g * 16;
#pragma unroll
        for (int t = 0; t < 10; t++) {
          const int cA = 8 * t, cB = 8 * t + 4;
          const int offA = (cA / 20) * 384 + ((cA % 20) >> 3) * 128 + ((cA % 20) & 7) * 2;
          const int offB = (cB / 20) * 384 + ((cB % 20) >> 3) * 128 + ((cB % 20) & 7) * 2;
          const uint32_t a = va + (q < 2 ? offA : offB) + (q & 1) * 4;
          const float* src = t < 8 ? &accM[64 + 4 * t] : &accR[16 + 4 * (t - 8)];
          sts32(a, pack2(src[0], src[1]));
          sts32(a + KV_ATOM, pack2(src[2], src[3]));
        }
        sts64(va + q * 384 + 256 + 8, 0x00003f80u, 0u);
        sts64(va + q * 384 + 256 + 8 + KV_ATOM, 0x00003f80u, 0u);
        fence_async_smem();
        mbar_arrive(BAR(B_KV + 4 + wg));
      }
      {
        const float sc = 0.22360679774997896f * 1.4426950408889634f;
        uint32_t qf[5][4];
#pragma unroll
        for (int u = 0; u < 5; u++) {
          const float* src = u < 4 ? &accM[8 * u] : &accR[0];
#pragma unroll
          for (int e = 0; e < 4; e++) qf[u][e] = pack2(src[2 * e] * sc, src[2 * e + 1] * sc);
        }
#pragma unroll
        for (int h = 0; h < 4; h++)
#pragma unroll
          for (int ks = 0; ks < 2; ks++)
#pragma unroll
            for (int e = 0; e < 4; e++) {
              const int lcA = 16 * ks + (e >> 1) * 8, lcB = lcA + 4;
              const bool vA = lcA >= 4 * h && lcA < 4 * h + 20, vB = lcB >= 4 * h && lcB < 4 * h + 20;
              qm[h][ks][e] = (q < 2 ? vA : vB) ? qf[h + ks][e] : 0u;
              asm volatile("" : "+r"(qm[h][ks][e]));
            }
      }
    }
    CSTAMP(4);
    {
      float O[4][12];
#pragma unroll
      for (int h = 0; h < 4; h++)
#pragma unroll
        for (int e = 0; e < 12; e++) O[h][e] = 0.f;
      const bool p0 = 2 * q <= g, p1 = 2 * q + 1 <= g;
      const uint32_t tri = (p0 ? 0xffffu : 0u) | (p1 ? 0xffff0000u : 0u);
      const int smin = bi >= 2 ? 0 : (bi == 1 ? 2 - wg : 4 - wg);
#pragma unroll 1
      for (int s = 4; s >= smin; s--) {
        const int t = wg + s;
        if (tid == 0) PSTAMP(104 + 2 * (4 - s));
        mbar_wait(BAR(B_KV + t), 0);
        if (tid == 0) PSTAMP(105 + 2 * (4 - s));
        const uint32_t kv = dlo(sb + (2 - (t >> 1)) * KV_IMG + (t & 1) * KV_HALF, KV_ATOM);
        uint32_t m[4][4];
#pragma unroll
        for (int u = 0; u < 4; u++) {
          const uint32_t inv = s == 0 ? ~0u : 0u, edge = (s == 4 || s == 0) ? ~0u : 0u;
          m[u][0] = ((u < wr ? ~0u : u == wr ? tri : 0u) ^ inv) | ~edge;
          m[u][1] = ((u <= wr ? ~0u : 0u) ^ inv) | ~edge;
          m[u][2] = ((u < wr ? ~0u : 0u) ^ inv) | ~edge;
          m[u][3] = m[u][1] | m[u][2];
        }
        att_fast_piece(O, qm, kv, m);
      }
      uint32_t redo;
      {
        float z = 0.f;
        bool ok = true;
#pragma unroll
        for (int h = 0; h < 4; h++) {
#pragma unroll
          for (int e = 0; e < 12; e++) z = fmaf(O[h][e], 0.f, z);
          ok = ok && (q != 2 || (O[h][8] >= 8.67e-19f && O[h][10] >= 8.67e-19f));
        }
        ok = ok && z == 0.f;
        asm volatile("{\n.reg .pred p, r;\nsetp.eq.u32 p, %1, 0;\nbar.red.or.pred r, %2, 128, p;\nselp.u32 %0, 1, 0, r;\n}"
                     : "=r"(redo) : "r"((uint32_t)ok), "r"(NB_VOTE + wg) : "memory");
      }
      uint32_t res[24];
      if (redo) {
        uint32_t tmp[24];
#pragma unroll 1
        for (int h = 0; h < 4; h++) {
          uint32_t qh[4][2][4];
#pragma unroll
          for (int e = 0; e < 8; e++) {
            const uint32_t v = h == 0 ? qm[0][e >> 2][e & 3] : h == 1 ? qm[1][e >> 2][e & 3] : h == 2 ? qm[2][e >> 2][e & 3] : qm[3][e >> 2][e & 3];
            qh[0][e >> 2][e & 3] = v;
            asm volatile("" : "+r"(qh[0][e >> 2][e & 3]));
          }
          float O2[12], S0[32], m0 = __int_as_float(0xff800000), m1 = m0;
          uint32_t P0[4][4];
#pragma unroll
          for (int e = 0; e < 12; e++) O2[e] = 0.f;
#pragma unroll 1
          for (int s = 4; s >= smin; s--) {
            const int t = wg + s;
            const uint32_t kv = dlo(sb + (2 - (t >> 1)) * KV_IMG + (t & 1) * KV_HALF, KV_ATOM);
            const bool diag = s == 4;
            qk_issue<0>(S0, qh, kv + h * 16);
            WG_WAIT(0);
            softmax_slab(S0, P0, O2, m0, m1, s == 0 ? wr : 0, diag ? wr : 3, (diag || s == 0) ? wr : -1, p0 == diag, p1 == diag, diag);
            pv_issue<0>(O2, P0, kv + h * 24);
            WG_WAIT(0);
          }
          att_norm(O2, &tmp[6 * h], lane);
        }
#pragma unroll
        for (int e = 0; e < 24; e++) res[e] = tmp[e];
      } else {
#pragma unroll
        for (int h = 0; h < 4; h++) att_norm(O[h], &res[6 * h], lane);
      }
      const uint32_t stg0 = sb + (wg ? KV_HALF : 2 * KV_IMG) + w * 4096, stg1 = stg0 + 2048;
      if (redo) bar_sync(NB_VOTE + wg, 128);
      CSTAMP(5);
#pragma unroll
      for (int h = 0; h < 4; h++)
#pragma unroll
        for (int t = 0; t < 3; t++) {
          const int c = 20 * h + 8 * t + 2 * q;
          if (t < 2 || q < 2) {
            const uint32_t a0 = c < 64 ? stg0 + g * 128 + (((c >> 3) ^ g) << 4) + (c & 7) * 2 : stg1 + g * 32 + (c - 64) * 2;
            sts32(a0, res[6 * h + 2 * t]);
            sts32(a0 + (c < 64 ? 1024 : 256), res[6 * h + 2 * t + 1]);
          }
        }
      __syncwarp();
      stage_to_global(stg0, stg1, (bf16*)g_o + (size_t)(bi * 128 + wg * 64 + wr * 16) * DM + bj * 80, lane);
      __syncwarp();
      if (lane == 0) mbar_arrive(BAR(B_OPUB));
    }
    CSTAMP(6);
    {
      uint4 xq[5];
      float acc[40];
      mbar_wait(BAR(B_WOB), 0);
      mbar_wait(BAR(B_AF), 0);
      CSTAMP(7);
      {
        const bf16* xs = p.x + (size_t)(bi * 128 + wg * 64 + w * 16) * DM + bj * 80;
#pragma unroll
        for (int m = 0; m < 4; m++) xq[m] = ldg_nc(xs + (m * 4 + (lane >> 3)) * DM + (lane & 7) * 8);
        xq[4] = ldg_nc(xs + (lane >> 1) * DM + 64 + (lane & 1) * 8);
      }
#pragma unroll 1
      for (int n = 0; n < 10; n++) {
        const int s = n & 3, kb = n < 8 ? 9 - n : n - 8;
        if (n == 8) mbar_wait(BAR(B_WOB + 1), 0);
        mbar_wait(BAR(B_AF + s), (n >> 2) & 1);
        const uint32_t as = dlo(sb + OFF_A + s * 16384 + wg * 8192, 16), bs = dlo(sb + OFF_WO + kb * 10240, 2048);
        WG_FENCE();
#pragma unroll
        for (int kk = 0; kk < 4; kk++)
          wgmma_ss_n80_t1(acc, mkdesc(as, kk * 32, 1024, 1), mkdesc(bs, kk * 512, 256, 3), (n | kk) != 0);
        WG_COMMIT();
        WG_WAIT(1);
        if (n > 0 && lane == 0) mbar_arrive(BAR(B_AE + ((n - 1) & 3)));
      }
      const uint32_t stg0 = sb + OFF_A + 32768 + wg * 8192 + w * 2048, stg1 = stg0 + 16384;
      mbar_wait(BAR(B_TAB2), 0);
#pragma unroll
      for (int m = 0; m < 4; m++) {
        const int row = m * 4 + (lane >> 3);
        sts128(stg0 + row * 128 + (((lane & 7) ^ (row & 7)) << 4), xq[m]);
      }
      sts128(stg1 + lane * 16, xq[4]);
      __syncwarp();
      uint32_t xo[5][4];
      uint4 gav[5];
      uint2 stb[5];
      const int frow = (lane & 7) + ((lane >> 3) & 1) * 8, fdh = lane >> 4;
#pragma unroll
      for (int u = 0; u < 5; u++) {
        ldsm4(xo[u], u < 4 ? stg0 + frow * 128 + (((2 * u + fdh) ^ (frow & 7)) << 4) : stg1 + frow * 32 + fdh * 16);
        stb[u] = lane < 24 ? lds64(sb + OFF_STB + u * 192 + lane * 8) : make_uint2(0u, 0u);
        gav[u] = lds128(sb + OFF_GA + u * 64 + q * 16);
      }
      WG_WAIT(0);
      CSTAMP(8);
      if (lane == 0) mbar_arrive(BAR(B_AE + 1));
#pragma unroll
      for (int u = 0; u < 5; u++) {
#pragma unroll
        for (int e = 0; e < 4; e++)
          xo[u][e] = pack2(fmaf(__uint_as_float(e < 2 ? gav[u].x : gav[u].z), acc[8 * u + 2 * e], bf_lo(xo[u][e])),
                           fmaf(__uint_as_float(e < 2 ? gav[u].y : gav[u].w), acc[8 * u + 2 * e + 1], bf_hi(xo[u][e])));
        stsm4(u < 4 ? stg0 + frow * 128 + (((2 * u + fdh) ^ (frow & 7)) << 4) : stg1 + frow * 32 + fdh * 16, xo[u][0], xo[u][1], xo[u][2], xo[u][3]);
      }
      __syncwarp();
      stage_to_global(stg0, stg1, (bf16*)g_x1 + (size_t)(bi * 128 + wg * 64 + w * 16) * DM + bj * 80, lane);
      __syncwarp();
      if (lane == 0) mbar_arrive(BAR(B_XPUB));
      if (tid == 0) PSTAMP(52);
      {
        float dl[4] = {0.f, 0.f, 0.f, 0.f}, dq[4] = {0.f, 0.f, 0.f, 0.f}, dr[4] = {0.f, 0.f, 0.f, 0.f};
#pragma unroll
        for (int u = 0; u < 5; u++) {
          uint32_t xh[4], xl[4];
#pragma unroll
          for (int e = 0; e < 4; e++) {
            xh[e] = hmul2(xo[u][e], xo[u][e]);
            xl[e] = hfma2(xo[u][e], xo[u][e], xh[e] ^ 0x80008000u);
          }
          mma16816(dl, xo[u], stb[u].x, stb[u].y);
          mma16816(dq, xh, stb[u].x, stb[u].y);
          mma16816(dr, xl, stb[u].x, stb[u].y);
        }
        const int src = lane & ~3;
        float o3[2][3];
#pragma unroll
        for (int r = 0; r < 2; r++) {
          const float lin = q == 0 ? dl[2 * r] : dl[2 * r] + dl[2 * r + 1];
          const float sq = q == 0 ? dq[2 * r] + dr[2 * r] : (dq[2 * r] + dq[2 * r + 1]) + (dr[2 * r] + dr[2 * r + 1]);
          const float gsx = __shfl_sync(~0u, lin, src + 2);
          o3[r][0] = lin; o3[r][1] = sq; o3[r][2] = q == 0 ? dl[2 * r + 1] : gsx;
        }
        if (q < 2) {
#pragma unroll
          for (int r = 0; r < 2; r++)
            ll_store16(&g_stats[(item * 2 + q) * 128 + wg * 64 + w * 16 + g + 8 * r], o3[r][0], o3[r][1], o3[r][2], ep1);
        }
        __syncwarp();
        if (lane == 0) mbar_arrive(BAR(B_SPUB));
      }
    }
    CSTAMP(9);
    uint32_t hfr[12][4];
    {
      float accM[96], accR[16];
#pragma unroll
      for (int t = 0; t < 28; t++) {
        const uint2 bv = lds64(sb + OFF_B1T + (8 * t + 2 * q) * 4);
        float* d = t < 24 ? &accM[4 * t] : &accR[4 * (t - 24)];
        d[0] = d[2] = __uint_as_float(bv.x);
        d[1] = d[3] = __uint_as_float(bv.y);
        asm volatile("" : "+f"(d[0]), "+f"(d[1]), "+f"(d[2]), "+f"(d[3]));
      }
      uint32_t ka[2], kb_[2], kr[2], kc[2];
      {
        const uint4* fp = &g_fin[bi * 128 + wg * 64 + wr * 16 + g];
        uint4 v0, v1;
        mbar_wait(BAR(B_FIN), 0);
        int it = 0;
        do {
          v0 = ll_load16(fp);
          v1 = ll_load16(fp + 8);
        } while ((v0.w != ep1 || v1.w != ep1) && ++it < SPIN_LIMIT);
        __syncwarp();
        ka[0] = __byte_perm(v0.x, 0, 0x1010); kb_[0] = __byte_perm(v0.x, 0, 0x3232);
        kr[0] = __byte_perm(v0.y, 0, 0x1010); kc[0] = __byte_perm(v0.y, 0, 0x3232);
        ka[1] = __byte_perm(v1.x, 0, 0x1010); kb_[1] = __byte_perm(v1.x, 0, 0x3232);
        kr[1] = __byte_perm(v1.y, 0, 0x1010); kc[1] = __byte_perm(v1.y, 0, 0x3232);
      }
      uint32_t af[2][4], raw[2][4];
      uint4 pr[2];
      const uint32_t tab = sb + OFF_TAB + q * 16;
      DSTAMP(56, ka[0] ^ kc[1]);
      mbar_wait(BAR(B_BF), 0);
      mbar_wait(BAR(B_AF + 2), 0);
      CSTAMP(10);
#pragma unroll
      for (int kk = 0; kk < 2; kk++) {
        ldsm4(raw[kk], sb + OFF_A + 2 * 16384 + a_off + (((2 * kk + a_hx) ^ a_rx) << 4));
        pr[kk] = lds128(tab + kk * 64);
      }
#pragma unroll 1
      for (int kb = 0; kb < 10; kb++) {
        const int n = 10 + kb, s = n & 3, sn = (n + 1) & 3, s5 = kb % 5;
        const uint32_t bs = dlo(sb + slot_b(s5), 8192);
#pragma unroll
        for (int kk = 0; kk < 4; kk++) {
          const int e = kk & 1;
          af[e][0] = hfma2(hfma2(raw[e][0], ka[0], kb_[0]), pr[e].x, hfma2(pr[e].y, kr[0], kc[0]));
          af[e][1] = hfma2(hfma2(raw[e][1], ka[1], kb_[1]), pr[e].x, hfma2(pr[e].y, kr[1], kc[1]));
          af[e][2] = hfma2(hfma2(raw[e][2], ka[0], kb_[0]), pr[e].z, hfma2(pr[e].w, kr[0], kc[0]));
          af[e][3] = hfma2(hfma2(raw[e][3], ka[1], kb_[1]), pr[e].z, hfma2(pr[e].w, kr[1], kc[1]));
          WG_FENCE();
          wgmma_rs_n32_t1(accR, af[e], mkdesc(bs, 24576 + kk * 1024, 512, 2), 1);
          wgmma_rs_n192_t1(accM, af[e], mkdesc(bs, kk * 2048, 1024, 1), 1);
          WG_COMMIT();
          if (kk < 2 || kb < 9) {
            if (kk == 2) {
              mbar_wait2(BAR(B_AF + sn), ((n + 1) >> 2) & 1, BAR(B_BF + (kb + 1) % 5), (kb + 1) / 5);
            }
            ldsm4(raw[e], sb + OFF_A + (kk < 2 ? s : sn) * 16384 + a_off + (((2 * ((kk + 2) & 3) + a_hx) ^ a_rx) << 4));
            pr[e] = lds128(tab + (kb * 4 + kk + 2) * 64);
          }
          WG_WAIT(1);
          if (kk == 0 && kb > 0 && lane == 0) {
            mbar_arrive(BAR(B_AE + ((n - 1) & 3)));
            mbar_arrive(BAR(B_BE + (kb + 4) % 5));
          }
        }
      }
      WG_WAIT(0);
      CSTAMP(11);
      if (lane == 0) {
        mbar_arrive(BAR(B_AE + 3));
        mbar_arrive(BAR(B_BE + 4));
        asm volatile("{\n.reg .b32 r;\nmapa.shared::cluster.u32 r, %0, %1;\nmbarrier.arrive.relaxed.cluster.shared::cluster.b64 _, [r];\n}"
                     ::"r"(BAR(B_PEER)), "r"(rank ^ 1u) : "memory");
      }
      __syncwarp();
      bar_sync(NB_CONS, 256);
      const int srow = wg * 64 + wr * 16 + (lane & 7) + ((lane >> 3) & 1) * 8;
      uint32_t hr[2][4];
#pragma unroll
      for (int part = 0; part < 3; part++) {
#pragma unroll
        for (int s = 4 * part; s < 4 * part + 4 + 2 * (part == 2); s++) {
          const float* src = s < 12 ? &accM[8 * s] : &accR[8 * (s - 12)];
#pragma unroll
          for (int e = 0; e < 4; e++) {
            const uint32_t v = gelu_half2(src[2 * e], src[2 * e + 1]);
            if (s < 12) { hfr[s][e] = v; asm volatile("" : "+r"(hfr[s][e])); } else { hr[s - 12][e] = fs >= 6 ? 0u : v; }
          }
        }
#pragma unroll
        for (int s = 4 * part; s < 4 * part + 4; s++)
          stsm4(sb + OFF_A + part * 16384 + srow * 128 + (((2 * (s & 3) + (lane >> 4)) ^ (srow & 7)) << 4), hfr[s][0], hfr[s][1], hfr[s][2], hfr[s][3]);
        if (part == 2) {
#pragma unroll
          for (int s = 0; s < 2; s++) stsm4(sb + OFF_A + 49152 + srow * 64 + (2 * s + (lane >> 4)) * 16, hr[s][0], hr[s][1], hr[s][2], hr[s][3]);
        }
        fence_async_smem();
        __syncwarp();
        if (lane == 0) mbar_arrive(BAR(B_HS + part));

        if (part < 2) mbar_wait(BAR(B_BF + part), 0);
      }
    }
    CSTAMP(12);
    {
      float accN[64], accS[16];
#pragma unroll
      for (int t = 0; t < 3; t++) {
        mbar_wait(BAR(B_BF + t), 0);
        const uint32_t bs = dlo(sb + slot_b(t), 8192);
        WG_FENCE();
#pragma unroll
        for (int kk = 0; kk < 4; kk++) {
          wgmma_rs_n32_t1(accS, hfr[4 * t + kk], mkdesc(bs, 16384 + kk * 1024, 512, 2), (t | kk) != 0);
          wgmma_rs_n128_t1(accN, hfr[4 * t + kk], mkdesc(bs, kk * 2048, 1024, 1), (t | kk) != 0);
        }
        WG_COMMIT();
        if (t > 0) {
          WG_WAIT(1);
          if (lane == 0) mbar_arrive(BAR(B_BE + t - 1));
        }
      }
      WG_WAIT(0);
      if (lane == 0) mbar_arrive(BAR(B_BE + 2));
      if (tid == 0) PSTAMP(114);
      uint32_t af[4][4];
      mbar_wait2(BAR(B_AF), 1, BAR(B_BF + 3), 0);
      if (tid == 0) PSTAMP(115);
#pragma unroll
      for (int kk = 0; kk < 2; kk++) ldsm4(af[kk], sb + OFF_A + a_off + (((2 * kk + a_hx) ^ a_rx) << 4));
#pragma unroll 1
      for (int t = 0; t < 11; t++) {
        const int n = 20 + t, s = n & 3, sn = (n + 1) & 3, m = 13 + t;
        const uint32_t bs = dlo(sb + slot_b(m % 5), 8192);
#pragma unroll
        for (int kk = 0; kk < 4; kk++) {
          WG_FENCE();
          wgmma_rs_n32_t1(accS, af[kk], mkdesc(bs, 16384 + kk * 1024, 512, 2), 1);
          wgmma_rs_n128_t1(accN, af[kk], mkdesc(bs, kk * 2048, 1024, 1), 1);
          WG_COMMIT();
          WG_WAIT(2);
          if (kk == 1 && t > 0 && lane == 0) {
            mbar_arrive(BAR(B_AE + ((n - 1) & 3)));
            mbar_arrive(BAR(B_BE + (m - 1) % 5));
          }
          if (kk < 2 || t < 10) {
            if (kk == 2) {
              mbar_wait2(BAR(B_AF + sn), ((n + 1) >> 2) & 1, BAR(B_BF + (m + 1) % 5), ((m + 1) / 5) & 1);
            }
            ldsm4(af[(kk + 2) & 3], sb + OFF_A + (kk < 2 ? s : sn) * 16384 + a_off + (((2 * ((kk + 2) & 3) + a_hx) ^ a_rx) << 4));
          }
        }
      }
      const int frow = wg * 64 + wr * 16 + (lane & 7) + ((lane >> 3) & 1) * 8;
      uint32_t xr[5][4], gbv[5][2], b2v[5][2];
      mbar_wait2(BAR(B_X1G), 0, BAR(B_PEER), 0);
#pragma unroll
      for (int u = 0; u < 5; u++) {
        ldsm4(xr[u], sb + slot_b(u) + 20480 + frow * 32 + (lane >> 4) * 16);
        gbv[u][0] = lds32(sb + OFF_GB + u * 32 + q * 4); gbv[u][1] = lds32(sb + OFF_GB + u * 32 + q * 4 + 16);
        b2v[u][0] = lds32(sb + OFF_B2 + u * 32 + q * 4); b2v[u][1] = lds32(sb + OFF_B2 + u * 32 + q * 4 + 16);
      }
      uint32_t peer;
      asm volatile("mapa.shared::cluster.u32 %0, %1, %2;" : "=r"(peer) : "r"(sb), "r"(rank ^ 1u));
      WG_WAIT(0);
      CSTAMP(13);
      float keep[40];
#pragma unroll
      for (int u = 0; u < 5; u++) {
        uint32_t w4[4];
#pragma unroll
        for (int e = 0; e < 8; e++) {
          const float lo = accN[8 * u + e], hi = u < 3 ? accN[40 + 8 * u + e] : accS[8 * (u - 3) + e];
          keep[8 * u + e] = rk ? hi : lo;
          if (e & 1) {
            const float lo0 = accN[8 * u + e - 1], hi0 = u < 3 ? accN[40 + 8 * u + e - 1] : accS[8 * (u - 3) + e - 1];
            w4[e >> 1] = pack2(rk ? lo0 : hi0, rk ? lo : hi);
          }
        }
        asm volatile("st.async.weak.shared::cluster.mbarrier::complete_tx::bytes.v4.b32 [%0], {%1,%2,%3,%4}, [%5];"
                     ::"r"(peer + slot_b(u) + 24576 + tid * 16), "r"(w4[0]), "r"(w4[1]), "r"(w4[2]), "r"(w4[3]),
                     "r"(peer + OFF_BAR + 8 * (B_RX + wg)) : "memory");
      }
      mbar_wait(BAR(B_RX + wg), 0);
      CSTAMP(14);
#pragma unroll
      for (int u = 0; u < 5; u++) {
        const uint4 pv = lds128(sb + slot_b(u) + 24576 + tid * 16);
        const uint32_t p4[4] = {pv.x, pv.y, pv.z, pv.w};
        uint32_t o4[4];
#pragma unroll
        for (int e = 0; e < 4; e++)
          o4[e] = pack2(fmaf(keep[8 * u + 2 * e] + bf_lo(p4[e]) + bf_lo(b2v[u][e >> 1]), bf_lo(gbv[u][e >> 1]), bf_lo(xr[u][e])),
                        fmaf(keep[8 * u + 2 * e + 1] + bf_hi(p4[e]) + bf_hi(b2v[u][e >> 1]), bf_hi(gbv[u][e >> 1]), bf_hi(xr[u][e])));
        stsm4(sb + slot_b(u) + 20480 + frow * 32 + (lane >> 4) * 16, o4[0], o4[1], o4[2], o4[3]);
      }
      __syncwarp();
      const int row0 = wg * 64 + wr * 16;
#pragma unroll
      for (int m = 0; m < 5; m++) {
        const int idx = lane + 32 * m, row = row0 + ((idx * 205) >> 11), ch = idx - ((idx * 205) >> 11) * 10;
        stg128(p.out + (size_t)(bi * 128 + row) * DM + (ch < 6 ? OUT_COL(0) : OUT_COL(3) - 48) + ch * 8,
               lds128(sb + slot_b(ch >> 1) + 20480 + row * 32 + (ch & 1) * 16));
      }
      CSTAMP(15);
      if (tid == 0) GSTAMP(127);
    }
  }
}

typedef CUresult (*EncodeFn)(CUtensorMap*, CUtensorMapDataType, cuuint32_t, void*, const cuuint64_t*, const cuuint64_t*,
                             const cuuint32_t*, const cuuint32_t*, CUtensorMapInterleave, CUtensorMapSwizzle,
                             CUtensorMapL2promotion, CUtensorMapFloatOOBfill);

void encode(EncodeFn fn, CUtensorMap* m, const void* base, int rank, const cuuint64_t* dims, const cuuint64_t* strides,
            const cuuint32_t* box, CUtensorMapSwizzle sw) {
  const cuuint32_t es[4] = {1, 1, 1, 1};
  fn(m, CU_TENSOR_MAP_DATA_TYPE_BFLOAT16, rank, const_cast<void*>(base), dims, strides, box, es, CU_TENSOR_MAP_INTERLEAVE_NONE, sw,
     CU_TENSOR_MAP_L2_PROMOTION_L2_128B, CU_TENSOR_MAP_FLOAT_OOB_FILL_NONE);
}

int active_clusters(int cs) {
  cudaLaunchConfig_t cfg = {};
  cfg.gridDim = dim3(cs * 16);
  cfg.blockDim = dim3(384);
  cfg.dynamicSmemBytes = SMEM_BYTES;
  cudaLaunchAttribute a[1];
  a[0].id = cudaLaunchAttributeClusterDimension;
  a[0].val.clusterDim.x = cs; a[0].val.clusterDim.y = 1; a[0].val.clusterDim.z = 1;
  cfg.attrs = a; cfg.numAttrs = 1;
  int n = 0;
  if (cudaOccupancyMaxActiveClusters(&n, fused_block_kernel, &cfg) != cudaSuccess) { (void)cudaGetLastError(); return -1; }
  return n;
}

}

extern "C" void kernel_launch(void* const* d_in, const int* in_sizes, int n_in, void* d_out, int out_size) {
  (void)in_sizes; (void)n_in; (void)out_size;
  static bool ready = false;
  static TMaps tm;
  static Params p;
  static const void* key[11];
  bool same = ready && key[10] == d_out;
  for (int i = 0; i < 10 && same; i++) same = key[i] == d_in[i];
  if (!same) {
    for (int i = 0; i < 10; i++) key[i] = d_in[i];
    key[10] = d_out;
    void* fp = nullptr;
    cudaDriverEntryPointQueryResult qr;
    cudaGetDriverEntryPoint("cuTensorMapEncodeTiled", &fp, cudaEnableDefault, &qr);
    EncodeFn fn = (EncodeFn)fp;
    void *o_ptr, *x1_ptr, *h_ptr;
    cudaGetSymbolAddress(&o_ptr, g_o);
    cudaGetSymbolAddress(&x1_ptr, g_x1);
    cudaGetSymbolAddress(&h_ptr, g_h);
    const void *x = d_in[0], *wqkv = d_in[1], *wo = d_in[2], *w1 = d_in[4], *w2 = d_in[6];
    {
      const cuuint64_t d[2] = {640, 2048}, s[1] = {1280};
      const cuuint32_t b[2] = {64, 128};
      encode(fn, &tm.x, x, 2, d, s, b, CU_TENSOR_MAP_SWIZZLE_128B);
      encode(fn, &tm.o, o_ptr, 2, d, s, b, CU_TENSOR_MAP_SWIZZLE_128B);
      encode(fn, &tm.x1, x1_ptr, 2, d, s, b, CU_TENSOR_MAP_SWIZZLE_128B);
      const cuuint32_t bg[2] = {16, 128}, br[2] = {32, 128};
      encode(fn, &tm.x1g, x1_ptr, 2, d, s, bg, CU_TENSOR_MAP_SWIZZLE_NONE);
      const cuuint64_t dh[2] = {HP, 2048}, sh[1] = {HP * 2};
      encode(fn, &tm.h, h_ptr, 2, dh, sh, b, CU_TENSOR_MAP_SWIZZLE_128B);
      encode(fn, &tm.h_r, h_ptr, 2, dh, sh, br, CU_TENSOR_MAP_SWIZZLE_NONE);
    }
    {
      const cuuint64_t d[3] = {640, 640, 3}, s[2] = {3840, 1280};
      const cuuint32_t bm[3] = {64, 64, 3}, br[3] = {16, 64, 3};
      encode(fn, &tm.wqkv_m, wqkv, 3, d, s, bm, CU_TENSOR_MAP_SWIZZLE_128B);
      encode(fn, &tm.wqkv_r, wqkv, 3, d, s, br, CU_TENSOR_MAP_SWIZZLE_32B);
    }
    {
      const cuuint64_t d[3] = {16, 640, 40}, s[2] = {1280, 32};
      const cuuint32_t b[3] = {16, 64, 5};
      encode(fn, &tm.wo, wo, 3, d, s, b, CU_TENSOR_MAP_SWIZZLE_32B);
    }
    {
      const cuuint64_t d[3] = {64, 640, 27}, s[2] = {3456, 128};
      const cuuint32_t b[3] = {64, 64, 3};
      encode(fn, &tm.w1_m, w1, 3, d, s, b, CU_TENSOR_MAP_SWIZZLE_128B);
      const cuuint64_t d2[2] = {1728, 640}, s2[1] = {3456};
      const cuuint32_t b2[2] = {32, 64};
      encode(fn, &tm.w1_r, w1, 2, d2, s2, b2, CU_TENSOR_MAP_SWIZZLE_64B);
    }
    {
      const cuuint64_t d3[3] = {64, 1728, 10}, s3[2] = {1280, 128}, d[2] = {640, 1728}, s[1] = {1280};
      const cuuint32_t bm[3] = {64, 64, 2}, bn[2] = {32, 64}, bk[2] = {64, 32}, bkn[2] = {32, 32};
      encode(fn, &tm.w2_m, w2, 3, d3, s3, bm, CU_TENSOR_MAP_SWIZZLE_128B);
      encode(fn, &tm.w2_n, w2, 2, d, s, bn, CU_TENSOR_MAP_SWIZZLE_64B);
      encode(fn, &tm.w2_k, w2, 2, d, s, bk, CU_TENSOR_MAP_SWIZZLE_128B);
      encode(fn, &tm.w2_kn, w2, 2, d, s, bkn, CU_TENSOR_MAP_SWIZZLE_64B);
    }
    {
      const cuuint64_t d[2] = {3840, 640}, s[1] = {7680};
      const cuuint32_t b[2] = {16, 160};
      encode(fn, &tm.wmod, d_in[9], 2, d, s, b, CU_TENSOR_MAP_SWIZZLE_NONE);
    }
    p.x = (const bf16*)x; p.wo = (const bf16*)wo; p.w1 = (const bf16*)w1; p.b1 = (const bf16*)d_in[5];
    p.w2 = (const bf16*)w2; p.b2 = (const bf16*)d_in[7]; p.c = (const bf16*)d_in[8];
    p.out = (bf16*)d_out;
    cudaFuncSetAttribute(fused_block_kernel, cudaFuncAttributeMaxDynamicSharedMemorySize, SMEM_BYTES);
    cudaFuncSetAttribute(fused_block_kernel, cudaFuncAttributeNonPortableClusterSizeAllowed, 1);
    int sms = 0;
    cudaDeviceGetAttribute(&sms, cudaDevAttrMultiProcessorCount, 0);
    p.use_smid = sms == NCTA && active_clusters(4) == 30 && active_clusters(8) == 15 && active_clusters(16) == 7;
    ready = true;
  }
  cudaLaunchConfig_t cfg = {};
  cfg.gridDim = dim3(NCTA);
  cfg.blockDim = dim3(384);
  cfg.dynamicSmemBytes = SMEM_BYTES;
  cfg.stream = cudaStreamPerThread;
  cudaLaunchAttribute at[1];
  at[0].id = cudaLaunchAttributeClusterDimension;
  at[0].val.clusterDim.x = 2; at[0].val.clusterDim.y = 1; at[0].val.clusterDim.z = 1;
  cfg.attrs = at; cfg.numAttrs = 1;
  cudaLaunchKernelEx(&cfg, fused_block_kernel, tm, p);
}
```
